```python
import torch

def _softmax(x, axis=-1):
    return torch.softmax(x, dim=axis)
def _gelu(x):
    return torch.nn.functional.gelu(x, approximate="tanh")
def _silu(x):
    return torch.nn.functional.silu(x)
def _sigmoid(x):
    return torch.sigmoid(x)
def _layernorm(x, axis=-1, eps=1e-5):
    m = x.mean(dim=axis, keepdim=True)
    v = x.var(dim=axis, keepdim=True, unbiased=False)
    return (x - m) / torch.sqrt(v + eps)
def _scatter_add(tgt, idx, src, axis=0):
    return tgt.clone().index_add_(axis, idx, src)
def _segment_sum(src, seg, n):
    out = torch.zeros((n,) + src.shape[1:], dtype=src.dtype)
    return out.index_add_(0, seg, src)
def _pad(x, pw):
    flat = tuple(v for pair in reversed(pw) for v in pair)
    return torch.nn.functional.pad(x, flat)

kernel_name = 'gated_mix__grouped_kv_mqa__dense_activation_silu__prompt'

def setup_inputs():

    _w = (lambda a: (lambda t: t.to(torch.bfloat16) if t.is_floating_point() else t)(torch.as_tensor(a)))
    def _A_setup():
        B, S, D, H = 1, 2048, 1024, 32
        Dh = D // H
        return {
            "x": _w((lambda *s: torch.randn(*s, dtype=torch.bfloat16) * 0.05)(B, S, D)),
            "wq": _w((lambda *s: torch.randn(*s, dtype=torch.bfloat16) * 0.8)(D, H * Dh)),
            "wk": _w((lambda *s: torch.randn(*s, dtype=torch.bfloat16) * 0.8)(D, Dh)),
            "wv": _w((lambda *s: torch.randn(*s, dtype=torch.bfloat16) * 0.05)(D, Dh)),
            "wo": _w((lambda *s: torch.randn(*s, dtype=torch.bfloat16) * 0.05)(H * Dh, D)),
        }
    _A_in = _A_setup()

    def _B_setup():
        B, S, D, F = 1, 2048, 1024, 3584
        return {
            "x": _w((lambda *s: torch.randn(*s, dtype=torch.bfloat16) * 0.05)(B, S, D)),
            "w1": _w((lambda *s: torch.randn(*s, dtype=torch.bfloat16) * 3.2)(D, F) * (D ** -0.5)),
            "w2": _w((lambda *s: torch.randn(*s, dtype=torch.bfloat16) * 0.4)(F, D) * (F ** -0.5)),
        }
    _B_in = _B_setup()

    return {
        "A_x": _A_in["x"],
        "A_wq": _A_in["wq"],
        "A_wk": _A_in["wk"],
        "A_wv": _A_in["wv"],
        "A_wo": _A_in["wo"],
        "B_x": _B_in["x"],
        "B_w1": _B_in["w1"],
        "B_w2": _B_in["w2"],
        "gate_w": _w((lambda *s: torch.randn(*s, dtype=torch.bfloat16) * 0.05)(1024) * 16.0),
    }

def reference(A_x, A_wq, A_wk, A_wv, A_wo, B_x, B_w1, B_w2, gate_w):
    def _A_ref(x, wq, wk, wv, wo):
        B, S, D = x.shape
        H = 32
        Dh = D // H
        q = (lambda x, *d: x.permute(*d))((x @ wq).reshape(B, S, H, Dh), 0, 2, 1, 3)
        k = x @ wk
        v = x @ wv
        scores = torch.einsum("bhqd,bkd->bhqk", q, k) * (Dh ** -0.5)
        p = _softmax(scores, axis=-1)
        o = torch.einsum("bhqk,bkd->bhqd", p, v)
        return (lambda x, *d: x.permute(*d))(o, 0, 2, 1, 3).reshape(B, S, H * Dh) @ wo

    def _B_ref(x, w1, w2):
        h = torch.einsum("bsd,df->bsf", x, w1)
        h = _silu(h)
        out = torch.einsum("bsf,fd->bsd", h, w2)
        return out

    x = A_x
    g = _sigmoid((x * gate_w).sum(-1, keepdims=True))
    a = _A_ref(x, A_wq, A_wk, A_wv, A_wo)
    b = _B_ref(x, B_w1, B_w2)
    return g * a + (1 - g) * b
```

```cpp
#include <cuda.h>
#include <cuda_bf16.h>
#include <cuda_runtime.h>
#include <stdint.h>

namespace {

constexpr int kCtas = 128;
constexpr int kThreads = 384;

constexpr int kPureHead = 4;
constexpr int kPureTail = 6;
constexpr int kItA = (16 - kPureHead) * 2;
constexpr int kItB = 32;
constexpr int kDouble = 128 - kItA - kItB - (68 - kPureTail);
static_assert(kItA < 31 && kItA % 2 == 0, "no row-tile boundary inside the n192 tile");
static_assert(kDouble >= 0 && kDouble + kPureTail <= 68 && kPureTail <= 12, "bad schedule");

constexpr uint32_t kSlotA = 49152, kSlotsA = 4;
constexpr uint32_t kSlotB = 32768, kSlotsB = 6;
constexpr uint32_t kSlotK = 8192, kSlotsK = 4;
constexpr uint32_t kOffKv = kSlotA * kSlotsA;
constexpr uint32_t kOffMisc = kOffKv + kSlotK * kSlotsK;
constexpr uint32_t kBarFullA = kOffMisc, kBarEmptyA = kBarFullA + 8 * kSlotsA;
constexpr uint32_t kBarFullB = kBarEmptyA + 8 * kSlotsA, kBarEmptyB = kBarFullB + 8 * kSlotsB;
constexpr uint32_t kBarFullK = kBarEmptyB + 8 * kSlotsB, kBarEmptyK = kBarFullK + 8 * kSlotsK;
constexpr uint32_t kBarEvent = kBarEmptyK + 8 * kSlotsK;
constexpr uint32_t kBarMeta = kBarEvent + 8 * 7;
constexpr uint32_t kBarSeen = kBarMeta + 8;
constexpr uint32_t kOffBound = kBarSeen + 8;
constexpr uint32_t kOffGate = kOffMisc + 512;
constexpr uint32_t kSmemBytes = kOffGate + 512 + 1024;
enum { kEvKv = 0, kEvHa = 1, kEvHb = 2, kEvO = 3 };

constexpr int kFlagKv = 0, kFlagDone = 32, kStat = 64, kFlagHa = kStat + 8 * 32, kFlagHb = kFlagHa + 16 * 32, kFlagO = kFlagHb + 16 * 32;
constexpr int kFlagWords = kFlagO + 64 * 32;
__device__ __align__(1024) uint8_t g_h[16 * 56 * 16384];
__device__ __align__(1024) uint8_t g_o[16 * 16 * 16384];
__device__ __align__(1024) uint8_t g_kv[32 * 8192];
__device__ __align__(1024) uint4 g_q[kCtas * 4 * 2 * 256];
__device__ __align__(1024) float g_gate[2048];
__device__ __align__(1024) unsigned g_flag[kFlagWords];

struct Maps {
  CUtensorMap x, wq, w1a, w1b, w2, wo, out;
};

constexpr float kScale = 0.25503487f;
constexpr float kMaxScore = 64.f;
constexpr float kMinV = 5.9604645e-08f, kMaxV = 1073741824.f;

__device__ __forceinline__ void mbar_init(uint32_t bar, uint32_t count) {
  asm volatile("mbarrier.init.shared::cta.b64 [%0], %1;" ::"r"(bar), "r"(count));
}
__device__ __forceinline__ void mbar_expect(uint32_t bar, uint32_t bytes) {
  asm volatile("mbarrier.arrive.expect_tx.shared::cta.b64 _, [%0], %1;" ::"r"(bar), "r"(bytes) : "memory");
}
__device__ __forceinline__ void mbar_arrive(uint32_t bar) {
  asm volatile("mbarrier.arrive.shared::cta.b64 _, [%0];" ::"r"(bar) : "memory");
}
__device__ __forceinline__ void mbar_wait(uint32_t bar, uint32_t parity) {
  asm volatile(
      "{\n.reg .pred p;\n.reg .u32 c;\n"
      "mbarrier.try_wait.parity.shared::cta.b64 p, [%0], %1;\n@p bra DONE;\nmov.u32 c, 0;\n"
      "LOOP:\nmbarrier.try_wait.parity.shared::cta.b64 p, [%0], %1;\n@p bra DONE;\n"
      "add.u32 c, c, 1;\nsetp.lt.u32 p, c, 0x80000;\n@p bra LOOP;\nDONE:\n}\n" ::"r"(bar), "r"(parity)
      : "memory");
}
__device__ __forceinline__ void mbar_wait2(uint32_t bar0, uint32_t parity0, uint32_t bar1, uint32_t parity1) {
  asm volatile(
      "{\n.reg .pred p, q;\n.reg .u32 c;\n"
      "mbarrier.try_wait.parity.shared::cta.b64 p, [%0], %1;\nmbarrier.try_wait.parity.shared::cta.b64 q, [%2], %3;\n"
      "and.pred p, p, q;\n@p bra DONE;\nmov.u32 c, 0;\n"
      "LOOP:\nmbarrier.try_wait.parity.shared::cta.b64 p, [%0], %1;\nmbarrier.try_wait.parity.shared::cta.b64 q, [%2], %3;\n"
      "and.pred p, p, q;\n@p bra DONE;\n"
      "add.u32 c, c, 1;\nsetp.lt.u32 p, c, 0x80000;\n@p bra LOOP;\nDONE:\n}\n" ::"r"(bar0), "r"(parity0), "r"(bar1), "r"(parity1)
      : "memory");
}
#define X_SIG 1
#define X_KVCOUNT (X_SIG == 2 ? kCtas * 8 : kCtas)
__device__ __forceinline__ void flag_wait(const unsigned* flag, unsigned target) {
  asm volatile(
      "{\n.reg .pred p;\n.reg .u32 c, v;\nmov.u32 c, 0;\n"
      "LOOP:\nld.acquire.gpu.global.u32 v, [%0];\nsetp.ge.u32 p, v, %1;\n@p bra DONE;\n"
      "add.u32 c, c, 1;\nsetp.lt.u32 p, c, 0x20000;\n@p bra LOOP;\nDONE:\n"
      "fence.proxy.async;\n}\n" ::"l"(flag), "r"(target)
      : "memory");
}
__device__ __forceinline__ void flag_signal(unsigned* flag) {
  asm volatile("red.release.gpu.global.add.u32 [%0], 1;" ::"l"(flag) : "memory");
}
__device__ __forceinline__ bool elect_one() {
  uint32_t p;
  asm volatile("{\n.reg .pred P;\nelect.sync _|P, 0xffffffff;\nselp.u32 %0, 1, 0, P;\n}\n" : "=r"(p));
  return p;
}
__device__ __forceinline__ void bulk_load(uint32_t dst, const void* src, uint32_t bytes, uint32_t bar) {
  asm volatile("cp.async.bulk.shared::cluster.global.mbarrier::complete_tx::bytes [%0], [%1], %2, [%3];" ::"r"(dst),
               "l"(src), "r"(bytes), "r"(bar)
               : "memory");
}
__device__ __forceinline__ void bulk_prefetch(const void* src, uint32_t bytes) {
  asm volatile("cp.async.bulk.prefetch.L2.global [%0], %1;" ::"l"(src), "r"(bytes) : "memory");
}
__device__ __forceinline__ void tma2(uint32_t dst, const CUtensorMap* m, int c0, int c1, uint32_t bar) {
  asm volatile("cp.async.bulk.tensor.2d.shared::cluster.global.mbarrier::complete_tx::bytes [%0], [%1, {%3, %4}], [%2];" ::"r"(dst),
               "l"(m), "r"(bar), "r"(c0), "r"(c1)
               : "memory");
}
__device__ __forceinline__ void tma3(uint32_t dst, const CUtensorMap* m, int c1, int c2, uint32_t bar) {
  asm volatile("cp.async.bulk.tensor.3d.shared::cluster.global.mbarrier::complete_tx::bytes [%0], [%1, {0, %3, %4}], [%2];" ::"r"(dst),
               "l"(m), "r"(bar), "r"(c1), "r"(c2)
               : "memory");
}
__device__ __forceinline__ void tma5(uint32_t dst, const CUtensorMap* m, int c2, int c3, int c4, uint32_t bar) {
  asm volatile("cp.async.bulk.tensor.5d.shared::cluster.global.mbarrier::complete_tx::bytes [%0], [%1, {0, 0, %3, %4, %5}], [%2];" ::"r"(dst),
               "l"(m), "r"(bar), "r"(c2), "r"(c3), "r"(c4)
               : "memory");
}
__device__ __forceinline__ void tma3_store(const CUtensorMap* m, uint32_t src, int c1, int c2) {
  asm volatile("cp.async.bulk.tensor.3d.global.shared::cta.bulk_group [%0, {0, %2, %3}], [%1];" ::"l"(m), "r"(src), "r"(c1), "r"(c2)
               : "memory");
}
__device__ __forceinline__ void prefetch_map(const CUtensorMap* m) {
  asm volatile("prefetch.tensormap [%0];" ::"l"(m) : "memory");
}
__device__ __forceinline__ void wg_fence() { asm volatile("wgmma.fence.sync.aligned;" ::: "memory"); }
__device__ __forceinline__ void wg_commit() { asm volatile("wgmma.commit_group.sync.aligned;" ::: "memory"); }
template <int N>
__device__ __forceinline__ void wg_wait() { asm volatile("wgmma.wait_group.sync.aligned %0;" ::"n"(N) : "memory"); }
template <int R>
__device__ __forceinline__ void pin(float (&a)[R]) {
#pragma unroll
  for (int i = 0; i < R; i++) asm volatile("" : "+f"(a[i])::"memory");
}
__device__ __forceinline__ uint64_t make_desc(uint32_t addr, uint32_t lbo, uint32_t sbo, uint32_t swizzle) {
  return (uint64_t)((addr & 0x3FFFF) >> 4) | ((uint64_t)(lbo >> 4) << 16) | ((uint64_t)(sbo >> 4) << 32) | ((uint64_t)swizzle << 62);
}
__device__ __forceinline__ float ex2(float x) {
  float y;
  asm("ex2.approx.ftz.f32 %0, %1;" : "=f"(y) : "f"(x));
  return y;
}
__device__ __forceinline__ float rcp(float x) {
  float y;
  asm("rcp.approx.ftz.f32 %0, %1;" : "=f"(y) : "f"(x));
  return y;
}
__device__ __forceinline__ float sigmoid(float x) { return rcp(1.f + ex2(x * -1.4426950408889634f)); }
__device__ __forceinline__ uint32_t pack2(float lo, float hi) {
  uint32_t r;
  asm("cvt.rn.bf16x2.f32 %0, %1, %2;" : "=r"(r) : "f"(hi), "f"(lo));
  return r;
}
__device__ __forceinline__ float bf_lo(uint32_t v) { return __uint_as_float(v << 16); }
__device__ __forceinline__ float bf_hi(uint32_t v) { return __uint_as_float(v & 0xffff0000u); }
__device__ __forceinline__ float lds_f32(uint32_t addr) {
  float v;
  asm volatile("ld.shared.f32 %0, [%1];" : "=f"(v) : "r"(addr) : "memory");
  return v;
}
__device__ __forceinline__ float quad_sum(float v) {
  v += __shfl_xor_sync(~0u, v, 1);
  return v + __shfl_xor_sync(~0u, v, 2);
}

__device__ __forceinline__ void wgmma_rs_n32(float (&d)[16], const uint32_t (&a)[4], uint64_t db, int accumulate) {
  asm volatile(
      "{\n.reg .pred p;\nsetp.ne.b32 p, %21, 0;\n"
      "wgmma.mma_async.sync.aligned.m64n32k16.f32.bf16.bf16 {"
      "%0, %1, %2, %3, %4, %5, %6, %7, %8, %9, %10, %11, %12, %13, %14, %15"
      "}, {%16, %17, %18, %19}, %20, p, 1, 1, 1;\n}\n"
      : "+f"(d[0]), "+f"(d[1]), "+f"(d[2]), "+f"(d[3]), "+f"(d[4]), "+f"(d[5]), "+f"(d[6]), "+f"(d[7]),
        "+f"(d[8]), "+f"(d[9]), "+f"(d[10]), "+f"(d[11]), "+f"(d[12]), "+f"(d[13]), "+f"(d[14]), "+f"(d[15])
      : "r"(a[0]), "r"(a[1]), "r"(a[2]), "r"(a[3]), "l"(db), "r"(accumulate));
}
__device__ __forceinline__ void wgmma_rs_n64(float (&d)[32], const uint32_t (&a)[4], uint64_t db, int accumulate) {
  asm volatile(
      "{\n.reg .pred p;\nsetp.ne.b32 p, %37, 0;\n"
      "wgmma.mma_async.sync.aligned.m64n64k16.f32.bf16.bf16 {"
      "%0, %1, %2, %3, %4, %5, %6, %7, %8, %9, %10, %11, %12, %13, %14, %15, "
      "%16, %17, %18, %19, %20, %21, %22, %23, %24, %25, %26, %27, %28, %29, %30, %31"
      "}, {%32, %33, %34, %35}, %36, p, 1, 1, 0;\n}\n"
      : "+f"(d[0]), "+f"(d[1]), "+f"(d[2]), "+f"(d[3]), "+f"(d[4]), "+f"(d[5]), "+f"(d[6]), "+f"(d[7]),
        "+f"(d[8]), "+f"(d[9]), "+f"(d[10]), "+f"(d[11]), "+f"(d[12]), "+f"(d[13]), "+f"(d[14]), "+f"(d[15]),
        "+f"(d[16]), "+f"(d[17]), "+f"(d[18]), "+f"(d[19]), "+f"(d[20]), "+f"(d[21]), "+f"(d[22]), "+f"(d[23]),
        "+f"(d[24]), "+f"(d[25]), "+f"(d[26]), "+f"(d[27]), "+f"(d[28]), "+f"(d[29]), "+f"(d[30]), "+f"(d[31])
      : "r"(a[0]), "r"(a[1]), "r"(a[2]), "r"(a[3]), "l"(db), "r"(accumulate));
}
__device__ __forceinline__ void wgmma_ss(float (&d)[64], uint64_t da, uint64_t db, int accumulate) {
  asm volatile(
      "{\n.reg .pred p;\nsetp.ne.b32 p, %66, 0;\n"
      "wgmma.mma_async.sync.aligned.m64n128k16.f32.bf16.bf16 {"
      "%0, %1, %2, %3, %4, %5, %6, %7, %8, %9, %10, %11, %12, %13, %14, %15, "
      "%16, %17, %18, %19, %20, %21, %22, %23, %24, %25, %26, %27, %28, %29, %30, %31, "
      "%32, %33, %34, %35, %36, %37, %38, %39, %40, %41, %42, %43, %44, %45, %46, %47, "
      "%48, %49, %50, %51, %52, %53, %54, %55, %56, %57, %58, %59, %60, %61, %62, %63"
      "}, %64, %65, p, 1, 1, 0, 1;\n}\n"
      : "+f"(d[0]), "+f"(d[1]), "+f"(d[2]), "+f"(d[3]), "+f"(d[4]), "+f"(d[5]), "+f"(d[6]), "+f"(d[7]),
        "+f"(d[8]), "+f"(d[9]), "+f"(d[10]), "+f"(d[11]), "+f"(d[12]), "+f"(d[13]), "+f"(d[14]), "+f"(d[15]),
        "+f"(d[16]), "+f"(d[17]), "+f"(d[18]), "+f"(d[19]), "+f"(d[20]), "+f"(d[21]), "+f"(d[22]), "+f"(d[23]),
        "+f"(d[24]), "+f"(d[25]), "+f"(d[26]), "+f"(d[27]), "+f"(d[28]), "+f"(d[29]), "+f"(d[30]), "+f"(d[31]),
        "+f"(d[32]), "+f"(d[33]), "+f"(d[34]), "+f"(d[35]), "+f"(d[36]), "+f"(d[37]), "+f"(d[38]), "+f"(d[39]),
        "+f"(d[40]), "+f"(d[41]), "+f"(d[42]), "+f"(d[43]), "+f"(d[44]), "+f"(d[45]), "+f"(d[46]), "+f"(d[47]),
        "+f"(d[48]), "+f"(d[49]), "+f"(d[50]), "+f"(d[51]), "+f"(d[52]), "+f"(d[53]), "+f"(d[54]), "+f"(d[55]),
        "+f"(d[56]), "+f"(d[57]), "+f"(d[58]), "+f"(d[59]), "+f"(d[60]), "+f"(d[61]), "+f"(d[62]), "+f"(d[63])
      : "l"(da), "l"(db), "r"(accumulate));
}
__device__ __forceinline__ void wgmma_ss(float (&d)[68], uint64_t da, uint64_t db, int accumulate) {
  asm volatile(
      "{\n.reg .pred p;\nsetp.ne.b32 p, %70, 0;\n"
      "wgmma.mma_async.sync.aligned.m64n136k16.f32.bf16.bf16 {"
      "%0, %1, %2, %3, %4, %5, %6, %7, %8, %9, %10, %11, %12, %13, %14, %15, "
      "%16, %17, %18, %19, %20, %21, %22, %23, %24, %25, %26, %27, %28, %29, %30, %31, "
      "%32, %33, %34, %35, %36, %37, %38, %39, %40, %41, %42, %43, %44, %45, %46, %47, "
      "%48, %49, %50, %51, %52, %53, %54, %55, %56, %57, %58, %59, %60, %61, %62, %63, "
      "%64, %65, %66, %67"
      "}, %68, %69, p, 1, 1, 0, 1;\n}\n"
      : "+f"(d[0]), "+f"(d[1]), "+f"(d[2]), "+f"(d[3]), "+f"(d[4]), "+f"(d[5]), "+f"(d[6]), "+f"(d[7]),
        "+f"(d[8]), "+f"(d[9]), "+f"(d[10]), "+f"(d[11]), "+f"(d[12]), "+f"(d[13]), "+f"(d[14]), "+f"(d[15]),
        "+f"(d[16]), "+f"(d[17]), "+f"(d[18]), "+f"(d[19]), "+f"(d[20]), "+f"(d[21]), "+f"(d[22]), "+f"(d[23]),
        "+f"(d[24]), "+f"(d[25]), "+f"(d[26]), "+f"(d[27]), "+f"(d[28]), "+f"(d[29]), "+f"(d[30]), "+f"(d[31]),
        "+f"(d[32]), "+f"(d[33]), "+f"(d[34]), "+f"(d[35]), "+f"(d[36]), "+f"(d[37]), "+f"(d[38]), "+f"(d[39]),
        "+f"(d[40]), "+f"(d[41]), "+f"(d[42]), "+f"(d[43]), "+f"(d[44]), "+f"(d[45]), "+f"(d[46]), "+f"(d[47]),
        "+f"(d[48]), "+f"(d[49]), "+f"(d[50]), "+f"(d[51]), "+f"(d[52]), "+f"(d[53]), "+f"(d[54]), "+f"(d[55]),
        "+f"(d[56]), "+f"(d[57]), "+f"(d[58]), "+f"(d[59]), "+f"(d[60]), "+f"(d[61]), "+f"(d[62]), "+f"(d[63]),
        "+f"(d[64]), "+f"(d[65]), "+f"(d[66]), "+f"(d[67])
      : "l"(da), "l"(db), "r"(accumulate));
}
__device__ __forceinline__ void wgmma_ss(float (&d)[96], uint64_t da, uint64_t db, int accumulate) {
  asm volatile(
      "{\n.reg .pred p;\nsetp.ne.b32 p, %98, 0;\n"
      "wgmma.mma_async.sync.aligned.m64n192k16.f32.bf16.bf16 {"
      "%0, %1, %2, %3, %4, %5, %6, %7, %8, %9, %10, %11, %12, %13, %14, %15, "
      "%16, %17, %18, %19, %20, %21, %22, %23, %24, %25, %26, %27, %28, %29, %30, %31, "
      "%32, %33, %34, %35, %36, %37, %38, %39, %40, %41, %42, %43, %44, %45, %46, %47, "
      "%48, %49, %50, %51, %52, %53, %54, %55, %56, %57, %58, %59, %60, %61, %62, %63, "
      "%64, %65, %66, %67, %68, %69, %70, %71, %72, %73, %74, %75, %76, %77, %78, %79, "
      "%80, %81, %82, %83, %84, %85, %86, %87, %88, %89, %90, %91, %92, %93, %94, %95"
      "}, %96, %97, p, 1, 1, 0, 1;\n}\n"
      : "+f"(d[0]), "+f"(d[1]), "+f"(d[2]), "+f"(d[3]), "+f"(d[4]), "+f"(d[5]), "+f"(d[6]), "+f"(d[7]),
        "+f"(d[8]), "+f"(d[9]), "+f"(d[10]), "+f"(d[11]), "+f"(d[12]), "+f"(d[13]), "+f"(d[14]), "+f"(d[15]),
        "+f"(d[16]), "+f"(d[17]), "+f"(d[18]), "+f"(d[19]), "+f"(d[20]), "+f"(d[21]), "+f"(d[22]), "+f"(d[23]),
        "+f"(d[24]), "+f"(d[25]), "+f"(d[26]), "+f"(d[27]), "+f"(d[28]), "+f"(d[29]), "+f"(d[30]), "+f"(d[31]),
        "+f"(d[32]), "+f"(d[33]), "+f"(d[34]), "+f"(d[35]), "+f"(d[36]), "+f"(d[37]), "+f"(d[38]), "+f"(d[39]),
        "+f"(d[40]), "+f"(d[41]), "+f"(d[42]), "+f"(d[43]), "+f"(d[44]), "+f"(d[45]), "+f"(d[46]), "+f"(d[47]),
        "+f"(d[48]), "+f"(d[49]), "+f"(d[50]), "+f"(d[51]), "+f"(d[52]), "+f"(d[53]), "+f"(d[54]), "+f"(d[55]),
        "+f"(d[56]), "+f"(d[57]), "+f"(d[58]), "+f"(d[59]), "+f"(d[60]), "+f"(d[61]), "+f"(d[62]), "+f"(d[63]),
        "+f"(d[64]), "+f"(d[65]), "+f"(d[66]), "+f"(d[67]), "+f"(d[68]), "+f"(d[69]), "+f"(d[70]), "+f"(d[71]),
        "+f"(d[72]), "+f"(d[73]), "+f"(d[74]), "+f"(d[75]), "+f"(d[76]), "+f"(d[77]), "+f"(d[78]), "+f"(d[79]),
        "+f"(d[80]), "+f"(d[81]), "+f"(d[82]), "+f"(d[83]), "+f"(d[84]), "+f"(d[85]), "+f"(d[86]), "+f"(d[87]),
        "+f"(d[88]), "+f"(d[89]), "+f"(d[90]), "+f"(d[91]), "+f"(d[92]), "+f"(d[93]), "+f"(d[94]), "+f"(d[95])
      : "l"(da), "l"(db), "r"(accumulate));
}
__device__ __forceinline__ void wgmma_ss(float (&d)[128], uint64_t da, uint64_t db, int accumulate) {
  asm volatile(
      "{\n.reg .pred p;\nsetp.ne.b32 p, %130, 0;\n"
      "wgmma.mma_async.sync.aligned.m64n256k16.f32.bf16.bf16 {"
      "%0, %1, %2, %3, %4, %5, %6, %7, %8, %9, %10, %11, %12, %13, %14, %15, "
      "%16, %17, %18, %19, %20, %21, %22, %23, %24, %25, %26, %27, %28, %29, %30, %31, "
      "%32, %33, %34, %35, %36, %37, %38, %39, %40, %41, %42, %43, %44, %45, %46, %47, "
      "%48, %49, %50, %51, %52, %53, %54, %55, %56, %57, %58, %59, %60, %61, %62, %63, "
      "%64, %65, %66, %67, %68, %69, %70, %71, %72, %73, %74, %75, %76, %77, %78, %79, "
      "%80, %81, %82, %83, %84, %85, %86, %87, %88, %89, %90, %91, %92, %93, %94, %95, "
      "%96, %97, %98, %99, %100, %101, %102, %103, %104, %105, %106, %107, %108, %109, %110, %111, "
      "%112, %113, %114, %115, %116, %117, %118, %119, %120, %121, %122, %123, %124, %125, %126, %127"
      "}, %128, %129, p, 1, 1, 0, 1;\n}\n"
      : "+f"(d[0]), "+f"(d[1]), "+f"(d[2]), "+f"(d[3]), "+f"(d[4]), "+f"(d[5]), "+f"(d[6]), "+f"(d[7]),
        "+f"(d[8]), "+f"(d[9]), "+f"(d[10]), "+f"(d[11]), "+f"(d[12]), "+f"(d[13]), "+f"(d[14]), "+f"(d[15]),
        "+f"(d[16]), "+f"(d[17]), "+f"(d[18]), "+f"(d[19]), "+f"(d[20]), "+f"(d[21]), "+f"(d[22]), "+f"(d[23]),
        "+f"(d[24]), "+f"(d[25]), "+f"(d[26]), "+f"(d[27]), "+f"(d[28]), "+f"(d[29]), "+f"(d[30]), "+f"(d[31]),
        "+f"(d[32]), "+f"(d[33]), "+f"(d[34]), "+f"(d[35]), "+f"(d[36]), "+f"(d[37]), "+f"(d[38]), "+f"(d[39]),
        "+f"(d[40]), "+f"(d[41]), "+f"(d[42]), "+f"(d[43]), "+f"(d[44]), "+f"(d[45]), "+f"(d[46]), "+f"(d[47]),
        "+f"(d[48]), "+f"(d[49]), "+f"(d[50]), "+f"(d[51]), "+f"(d[52]), "+f"(d[53]), "+f"(d[54]), "+f"(d[55]),
        "+f"(d[56]), "+f"(d[57]), "+f"(d[58]), "+f"(d[59]), "+f"(d[60]), "+f"(d[61]), "+f"(d[62]), "+f"(d[63]),
        "+f"(d[64]), "+f"(d[65]), "+f"(d[66]), "+f"(d[67]), "+f"(d[68]), "+f"(d[69]), "+f"(d[70]), "+f"(d[71]),
        "+f"(d[72]), "+f"(d[73]), "+f"(d[74]), "+f"(d[75]), "+f"(d[76]), "+f"(d[77]), "+f"(d[78]), "+f"(d[79]),
        "+f"(d[80]), "+f"(d[81]), "+f"(d[82]), "+f"(d[83]), "+f"(d[84]), "+f"(d[85]), "+f"(d[86]), "+f"(d[87]),
        "+f"(d[88]), "+f"(d[89]), "+f"(d[90]), "+f"(d[91]), "+f"(d[92]), "+f"(d[93]), "+f"(d[94]), "+f"(d[95]),
        "+f"(d[96]), "+f"(d[97]), "+f"(d[98]), "+f"(d[99]), "+f"(d[100]), "+f"(d[101]), "+f"(d[102]), "+f"(d[103]),
        "+f"(d[104]), "+f"(d[105]), "+f"(d[106]), "+f"(d[107]), "+f"(d[108]), "+f"(d[109]), "+f"(d[110]), "+f"(d[111]),
        "+f"(d[112]), "+f"(d[113]), "+f"(d[114]), "+f"(d[115]), "+f"(d[116]), "+f"(d[117]), "+f"(d[118]), "+f"(d[119]),
        "+f"(d[120]), "+f"(d[121]), "+f"(d[122]), "+f"(d[123]), "+f"(d[124]), "+f"(d[125]), "+f"(d[126]), "+f"(d[127])
      : "l"(da), "l"(db), "r"(accumulate));
}

struct Ring {
  uint32_t slot, phase;
  int prev;
};
struct Attn {
  float S[32], O[16];
  uint32_t P[4][4], Q[2][4];
  float l0, l1, m0, m1;
  uint32_t slot, phase;
  int it;
};
struct Ctx {
  uint32_t smem;
  int wg, warp, lane, rb, cb;
  bool leader;
};

template <bool B> struct RingCfg;
template <> struct RingCfg<false> { static constexpr uint32_t size = kSlotA, slots = kSlotsA, full = kBarFullA, empty = kBarEmptyA; };
template <> struct RingCfg<true> { static constexpr uint32_t size = kSlotB, slots = kSlotsB, full = kBarFullB, empty = kBarEmptyB; };

template <bool B>
__device__ __forceinline__ void ring_release_prev(const Ctx& c, Ring& r) {
  if (r.prev >= 0 && c.leader) mbar_arrive(c.smem + RingCfg<B>::empty + 8 * r.prev);
}
template <bool B>
__device__ __forceinline__ void ring_advance(Ring& r) {
  r.prev = r.slot;
  if (++r.slot == RingCfg<B>::slots) { r.slot = 0; r.phase ^= 1; }
}
template <bool B>
__device__ __forceinline__ uint64_t desc_a(const Ctx& c, const Ring& r) {
  const uint32_t addr = c.smem + c.wg * 8192;
  return (B ? make_desc(addr, 128, 1024, 0) : make_desc(addr, 16, 1024, 1)) + r.slot * (RingCfg<B>::size >> 4);
}
template <bool B>
__device__ __forceinline__ uint64_t desc_b(const Ctx& c, const Ring& r) {
  return make_desc(c.smem + 16384, 8192, 1024, 1) + r.slot * (RingCfg<B>::size >> 4);
}
template <bool B, int K0, int K1, int R>
__device__ __forceinline__ void gemm_steps(float (&acc)[R], uint64_t da, uint64_t db, int accumulate) {
#pragma unroll
  for (int k = K0; k < K1; k++) wgmma_ss(acc, da + k * (B ? 16 : 2), db + k * 128, k == 0 ? accumulate : 1);
}
template <bool B, int R>
__device__ __forceinline__ void stage_pure(const Ctx& c, Ring& r, float (&acc)[R], int accumulate) {
  mbar_wait(c.smem + RingCfg<B>::full + 8 * r.slot, r.phase);
  wg_fence();
  gemm_steps<B, 0, 4>(acc, desc_a<B>(c, r), desc_b<B>(c, r), accumulate);
  wg_commit();
  wg_wait<1>();
  ring_release_prev<B>(c, r);
  ring_advance<B>(r);
}
template <bool B>
__device__ __forceinline__ void ring_drain(const Ctx& c, Ring& r) {
  wg_wait<0>();
  ring_release_prev<B>(c, r);
  r.prev = -1;
}
__device__ __forceinline__ void event_arrive(const Ctx& c, int ev) {
  __syncwarp();
  if (c.lane == 0) mbar_arrive(c.smem + kBarEvent + 8 * ev);
}

__device__ __forceinline__ void attn_finish(const Ctx& c, Attn& a) {
  const int round = (a.it - 1) >> 5;
  const uint32_t ga = c.smem + kOffGate + (c.wg * 64 + c.warp * 16 + (c.lane >> 2)) * 4;
  const float s0 = __fdividef(lds_f32(ga), quad_sum(a.l0));
  const float s1 = __fdividef(lds_f32(ga + 32), quad_sum(a.l1));
  uint8_t* dst = g_o + (size_t)(c.rb * 16 + round * 4 + (c.cb >> 1)) * 16384 + (c.wg * 8 + c.warp * 2) * 1024 + (c.cb & 1) * 512 + c.lane * 4;
#pragma unroll
  for (int j = 0; j < 4; j++) {
    *reinterpret_cast<uint32_t*>(dst + j * 128) = pack2(a.O[4 * j] * s0, a.O[4 * j + 1] * s0);
    *reinterpret_cast<uint32_t*>(dst + j * 128 + 1024) = pack2(a.O[4 * j + 2] * s1, a.O[4 * j + 3] * s1);
  }
  event_arrive(c, kEvO + round);
  a.l0 = 0.f;
  a.l1 = 0.f;
}
__device__ __forceinline__ void attn_load_q(Attn& a) {
  const uint4* src = g_q + (blockIdx.x * 128 + a.it + 1) * 16 + threadIdx.x;
  const uint4 q0 = __ldcg(src), q1 = __ldcg(src + 256);
  a.Q[0][0] = q0.x; a.Q[0][1] = q0.y; a.Q[0][2] = q0.z; a.Q[0][3] = q0.w;
  a.Q[1][0] = q1.x; a.Q[1][1] = q1.y; a.Q[1][2] = q1.z; a.Q[1][3] = q1.w;
}
__device__ __forceinline__ void attn_pv(const Ctx& c, Attn& a, int accumulate) {
  const uint64_t dv = make_desc(c.smem + kOffKv + 4096, 512, 128, 0) + a.slot * (kSlotK >> 4);
#pragma unroll
  for (int t = 0; t < 4; t++) wgmma_rs_n32(a.O, a.P[t], dv + t * 64, t == 0 ? accumulate : 1);
}

template <bool FAST, bool B, int K0, int K1, bool MAY_FINISH, bool MAY_RELOAD, int R>
__device__ __forceinline__ void attn_step(const Ctx& c, Attn& a, Ring& r, float (&acc)[R], int accumulate, bool more = true) {
  const int j = a.it & 31;
  const uint64_t dk = make_desc(c.smem + kOffKv, 128, 512, 0) + a.slot * (kSlotK >> 4);
  wg_fence();
  wgmma_rs_n64(a.S, a.Q[0], dk, 0);
  wgmma_rs_n64(a.S, a.Q[1], dk + 16, 1);
  wg_commit();
  attn_pv(c, a, j != 1 && a.it != 0);
  wg_commit();
  gemm_steps<B, K0, K1>(acc, desc_a<B>(c, r), desc_b<B>(c, r), accumulate);
  wg_commit();
  wg_wait<2>();
  if (K0 == 0) ring_release_prev<B>(c, r);
  if (K1 == 4) ring_advance<B>(r);
  pin(a.S);
  if (MAY_RELOAD && j == 31 && a.it < 127) attn_load_q(a);
  const uint32_t kv_empty = c.smem + kBarEmptyK + 8 * a.slot;
  if (++a.slot == kSlotsK) { a.slot = 0; a.phase ^= 1; }
  float s0, s1, s2, s3;
  if (FAST) {
    float e[8];
#pragma unroll
    for (int i = 0; i < 8; i++) e[i] = ex2(a.S[i]);
    wg_wait<1>();
    if (c.leader) mbar_arrive(kv_empty);
#pragma unroll
    for (int i = 0; i < 32; i += 4) {
      const float p0 = i < 8 ? e[i] : ex2(a.S[i]), p1 = i < 8 ? e[i + 1] : ex2(a.S[i + 1]);
      const float p2 = i < 8 ? e[i + 2] : ex2(a.S[i + 2]), p3 = i < 8 ? e[i + 3] : ex2(a.S[i + 3]);
      if (i == 0) { s0 = p0; s1 = p1; s2 = p2; s3 = p3; } else { s0 += p0; s1 += p1; s2 += p2; s3 += p3; }
      a.P[i / 8][(i % 8) / 2] = pack2(p0, p1);
      a.P[i / 8][(i % 8) / 2 + 1] = pack2(p2, p3);
    }
  } else {
    wg_wait<1>();
    if (c.leader) mbar_arrive(kv_empty);
    pin(a.O);
    if (MAY_FINISH && j == 0) { attn_finish(c, a); a.m0 = -INFINITY; a.m1 = -INFINITY; }
    float x0 = a.m0, x1 = a.m1;
#pragma unroll
    for (int i = 0; i < 32; i += 4) {
      x0 = fmaxf(x0, fmaxf(a.S[i], a.S[i + 1]));
      x1 = fmaxf(x1, fmaxf(a.S[i + 2], a.S[i + 3]));
    }
    x0 = fmaxf(x0, __shfl_xor_sync(~0u, x0, 1));
    x1 = fmaxf(x1, __shfl_xor_sync(~0u, x1, 1));
    x0 = fmaxf(x0, __shfl_xor_sync(~0u, x0, 2));
    x1 = fmaxf(x1, __shfl_xor_sync(~0u, x1, 2));
    const float a0 = ex2(a.m0 - x0), a1 = ex2(a.m1 - x1);
    a.m0 = x0;
    a.m1 = x1;
    a.l0 *= a0;
    a.l1 *= a1;
#pragma unroll
    for (int i = 0; i < 16; i += 4) { a.O[i] *= a0; a.O[i + 1] *= a0; a.O[i + 2] *= a1; a.O[i + 3] *= a1; }
#pragma unroll
    for (int i = 0; i < 32; i += 4) {
      const float p0 = ex2(a.S[i] - x0), p1 = ex2(a.S[i + 1] - x0), p2 = ex2(a.S[i + 2] - x1), p3 = ex2(a.S[i + 3] - x1);
      if (i == 0) { s0 = p0; s1 = p1; s2 = p2; s3 = p3; } else { s0 += p0; s1 += p1; s2 += p2; s3 += p3; }
      a.P[i / 8][(i % 8) / 2] = pack2(p0, p1);
      a.P[i / 8][(i % 8) / 2 + 1] = pack2(p2, p3);
    }
  }
  if (K1 == 4) mbar_wait2(c.smem + kBarFullK + 8 * a.slot, a.phase, c.smem + RingCfg<B>::full + 8 * r.slot, r.phase ^ !more);
  else mbar_wait(c.smem + kBarFullK + 8 * a.slot, a.phase);
  if (FAST && MAY_FINISH && j == 0) { pin(a.O); attn_finish(c, a); }
  a.l0 += s0 + s1;
  a.l1 += s2 + s3;
  a.it++;
}

__device__ __forceinline__ void silu4(float& v0, float& v1, float& v2, float& v3) {
  constexpr float kNegLog2e = -1.4426950408889634f;
  const float t0 = ex2(fabsf(v0) * kNegLog2e), t1 = ex2(fabsf(v1) * kNegLog2e);
  const float t2 = ex2(fabsf(v2) * kNegLog2e), t3 = ex2(fabsf(v3) * kNegLog2e);
  const float d0 = 1.f + t0, d1 = 1.f + t1, d2 = 1.f + t2, d3 = 1.f + t3;
  const float d01 = d0 * d1, d23 = d2 * d3;
  const float r = rcp(d01 * d23);
  const float r01 = r * d23, r23 = r * d01;
  v0 = fmaxf(v0, v0 * t0) * d1 * r01;
  v1 = fmaxf(v1, v1 * t1) * d0 * r01;
  v2 = fmaxf(v2, v2 * t2) * d3 * r23;
  v3 = fmaxf(v3, v3 * t3) * d2 * r23;
}
template <int R>
__device__ __forceinline__ void store_h(const Ctx& c, float (&acc)[R], int first_stage, int ev) {
  pin(acc);
  uint8_t* dst = g_h + (size_t)(c.rb * 56 + first_stage) * 16384 + (c.wg * 8 + c.warp * 2) * 1024 + c.lane * 4;
#pragma unroll
  for (int j = 0; j < R / 4; j++) {
    float v0 = acc[4 * j], v1 = acc[4 * j + 1], v2 = acc[4 * j + 2], v3 = acc[4 * j + 3];
    silu4(v0, v1, v2, v3);
    uint8_t* p = dst + (j >> 3) * 16384 + (j & 7) * 128;
    *reinterpret_cast<uint32_t*>(p) = pack2(v0, v1);
    *reinterpret_cast<uint32_t*>(p + 1024) = pack2(v2, v3);
  }
  event_arrive(c, ev);
}

template <bool FAST>
__device__ __forceinline__ void consumer_main(const Maps& maps, const Ctx& c, Attn& a, Ring& r, float (&acc_a)[96]) {
  mbar_wait2(c.smem + kBarFullK, 0, c.smem + kBarFullA + 8 * r.slot, r.phase);
#pragma unroll 1
  for (int s = kPureHead; s < 16; s++) {
    attn_step<FAST, false, 0, 2, false, false>(c, a, r, acc_a, 1);
    attn_step<FAST, false, 2, 4, false, false>(c, a, r, acc_a, 1);
  }
  ring_drain<false>(c, r);
  store_h(c, acc_a, c.cb * 3, kEvHa);
  {
    float acc[128];
#pragma unroll 1
    for (int s = 0; s < 16; s++) {
      attn_step<FAST, false, 0, 2, true, false>(c, a, r, acc, s != 0);
      attn_step<FAST, false, 2, 4, false, true>(c, a, r, acc, 1, s != 15);
    }
    ring_drain<false>(c, r);
    store_h(c, acc, 24 + c.cb * 4, kEvHb);
  }
  float acc[64];
  r.slot = 0;
  r.phase = 0;
  mbar_wait(c.smem + kBarFullB, 0);
#pragma unroll 1
  for (int s = 0; s < kDouble; s++) {
    attn_step<FAST, true, 0, 2, true, false>(c, a, r, acc, s != 0);
    attn_step<FAST, true, 2, 4, false, true>(c, a, r, acc, 1);
  }
#pragma unroll 1
  for (int s = kDouble; s < 68 - kPureTail; s++) {
    if (s == 56) {
      wg_wait<0>();
      pin(acc);
      const uint32_t ga = c.smem + kOffGate + (c.wg * 64 + c.warp * 16 + (c.lane >> 2)) * 4;
      const float k0 = 1.f - lds_f32(ga), k1 = 1.f - lds_f32(ga + 32);
#pragma unroll
      for (int i = 0; i < 64; i += 4) { acc[i] *= k0; acc[i + 1] *= k0; acc[i + 2] *= k1; acc[i + 3] *= k1; }
    }
    attn_step<FAST, true, 0, 4, true, true>(c, a, r, acc, s != 0);
  }
  wg_fence();
  attn_pv(c, a, 1);
  wg_commit();
  wg_wait<0>();
  pin(a.O);
  attn_finish(c, a);
#pragma unroll 1
  for (int s = 68 - kPureTail; s < 72; s++) stage_pure<true>(c, r, acc, 1);
  wg_wait<0>();
  pin(acc);
  const uint32_t stage = c.smem + kOffKv + c.wg * 16384;
  const int row = c.warp * 16 + (c.lane & 15);
#pragma unroll
  for (int j = 0; j < 16; j += 2) {
    const int col = j + (c.lane >> 4);
    const uint32_t addr = stage + (col >> 3) * 8192 + row * 128 + (((col & 7) ^ (row & 7)) << 4);
    asm volatile("stmatrix.sync.aligned.m8n8.x4.shared.b16 [%0], {%1, %2, %3, %4};" ::"r"(addr),
                 "r"(pack2(acc[4 * j], acc[4 * j + 1])), "r"(pack2(acc[4 * j + 2], acc[4 * j + 3])),
                 "r"(pack2(acc[4 * j + 4], acc[4 * j + 5])), "r"(pack2(acc[4 * j + 6], acc[4 * j + 7]))
                 : "memory");
  }
  asm volatile("fence.proxy.async.shared::cta;" ::: "memory");
  asm volatile("bar.sync %0, 128;" ::"r"(1 + c.wg) : "memory");
  if (c.leader) {
    tma3_store(&maps.out, stage, c.rb * 128 + c.wg * 64, c.cb * 2);
    asm volatile("cp.async.bulk.commit_group;\ncp.async.bulk.wait_group.read 0;" ::: "memory");
  }
}

__device__ __forceinline__ void consumer(const Maps& maps, const Ctx& c, const __nv_bfloat16* x, const __nv_bfloat16* gate_w) {
  Ring r{0, 0, -1};
  Attn a;
  float qmax;
  {
    const int tok = c.rb * 128 + c.cb * 16 + (c.wg * 4 + c.warp) * 2;
    uint4 xa[4], xb[4], gw[4];
#pragma unroll
    for (int i = 0; i < 4; i++) {
      xa[i] = __ldg(reinterpret_cast<const uint4*>(x + (size_t)tok * 1024) + i * 32 + c.lane);
      xb[i] = __ldg(reinterpret_cast<const uint4*>(x + (size_t)(tok + 1) * 1024) + i * 32 + c.lane);
      gw[i] = __ldg(reinterpret_cast<const uint4*>(gate_w) + i * 32 + c.lane);
    }
    float acc[68];
    stage_pure<false>(c, r, acc, 0);
    float d0 = 0.f, d1 = 0.f;
#pragma unroll
    for (int i = 0; i < 4; i++) {
      const uint32_t wa[4] = {gw[i].x, gw[i].y, gw[i].z, gw[i].w};
      const uint32_t ua[4] = {xa[i].x, xa[i].y, xa[i].z, xa[i].w};
      const uint32_t ub[4] = {xb[i].x, xb[i].y, xb[i].z, xb[i].w};
#pragma unroll
      for (int k = 0; k < 4; k++) {
        d0 = fmaf(bf_lo(ua[k]), bf_lo(wa[k]), fmaf(bf_hi(ua[k]), bf_hi(wa[k]), d0));
        d1 = fmaf(bf_lo(ub[k]), bf_lo(wa[k]), fmaf(bf_hi(ub[k]), bf_hi(wa[k]), d1));
      }
    }
#pragma unroll
    for (int o = 16; o > 0; o >>= 1) {
      d0 += __shfl_xor_sync(~0u, d0, o);
      d1 += __shfl_xor_sync(~0u, d1, o);
    }
    if (c.lane < 2) g_gate[tok + c.lane] = sigmoid(c.lane ? d1 : d0);
#pragma unroll 1
    for (int s = 1; s < 16; s++) stage_pure<false>(c, r, acc, 1);
    ring_drain<false>(c, r);
    pin(acc);
    const bool is_v = c.cb >= 4;
    const uint32_t u0 = pack2(acc[64], acc[65]), u1 = pack2(acc[66], acc[67]);
    uint8_t* kv = g_kv + ((c.rb * 2 + c.wg + is_v) & 31) * 8192 + is_v * 4096 + c.warp * 1024 + (c.cb & 3) * 128 + c.lane * 4;
    *reinterpret_cast<uint32_t*>(kv) = u0;
    *reinterpret_cast<uint32_t*>(kv + 512) = u1;
    float st;
    if (is_v) {
      st = fmaxf(fmaxf(fabsf(bf_lo(u0)), fabsf(bf_hi(u0))), fmaxf(fabsf(bf_lo(u1)), fabsf(bf_hi(u1))));
      if (!(acc[64] + acc[65] + acc[66] + acc[67] < INFINITY)) st = INFINITY;
    } else {
      const float n0 = quad_sum(bf_lo(u0) * bf_lo(u0) + bf_hi(u0) * bf_hi(u0));
      const float n1 = quad_sum(bf_lo(u1) * bf_lo(u1) + bf_hi(u1) * bf_hi(u1));
      st = (n0 + n1 < INFINITY) ? fmaxf(n0, n1) : INFINITY;
    }
#pragma unroll
    for (int o = 16; o > 0; o >>= 1) st = fmaxf(st, __shfl_xor_sync(~0u, st, o));
    if (c.lane == 0) atomicMax(g_flag + kStat + c.cb * 32, __float_as_uint(st));
    event_arrive(c, kEvKv);
    qmax = 0.f;
#pragma unroll
    for (int h = 0; h < 4; h++) {
      uint32_t f[8];
      float n0 = 0.f, n1 = 0.f;
#pragma unroll
      for (int i = 0; i < 8; i++) {
        f[i] = pack2(acc[16 * h + 2 * i] * kScale, acc[16 * h + 2 * i + 1] * kScale);
        const float t = bf_lo(f[i]) * bf_lo(f[i]) + bf_hi(f[i]) * bf_hi(f[i]);
        if (i & 1) n1 += t; else n0 += t;
      }
      n0 = quad_sum(n0);
      n1 = quad_sum(n1);
      qmax = (n0 + n1 < INFINITY) ? fmaxf(qmax, fmaxf(n0, n1)) : INFINITY;
      if (h == 0) {
#pragma unroll
        for (int i = 0; i < 8; i++) a.Q[i / 4][i % 4] = f[i];
      } else {
        uint4* dst = g_q + ((size_t)blockIdx.x * 4 + h) * 512 + threadIdx.x;
        dst[0] = make_uint4(f[0], f[1], f[2], f[3]);
        dst[256] = make_uint4(f[4], f[5], f[6], f[7]);
      }
    }
  }
  float acc_a[96];
#pragma unroll 1
  for (int s = 0; s < kPureHead; s++) stage_pure<false>(c, r, acc_a, s != 0);
#pragma unroll
  for (int i = 0; i < 16; i++) a.P[i / 4][i % 4] = 0;
  a.l0 = 0.f; a.l1 = 0.f; a.m0 = -INFINITY; a.m1 = -INFINITY;
  a.slot = 0; a.phase = 0; a.it = 0;
  mbar_wait(c.smem + kBarMeta, 0);
  const bool ok = qmax * lds_f32(c.smem + kOffBound) * 1.02f <= kMaxScore * kMaxScore;
  uint32_t all_ok;
  asm volatile("{\n.reg .pred p, q;\nsetp.ne.u32 p, %1, 0;\nbar.red.and.pred q, %2, 128, p;\nselp.u32 %0, 1, 0, q;\n}\n"
               : "=r"(all_ok) : "r"((uint32_t)ok), "r"(1 + c.wg) : "memory");
  wg_wait<0>();
  if (__shfl_sync(~0u, all_ok, 0)) consumer_main<true>(maps, c, a, r, acc_a);
  else consumer_main<false>(maps, c, a, r, acc_a);
}

__device__ __forceinline__ void gemm_producer(const Maps& maps, uint32_t smem, int rb, int cb) {
  uint32_t slot = 0, phase = 1;
#pragma unroll 1
  for (int s = 0; s < 48; s++) {
    const uint32_t full = smem + kBarFullA + 8 * slot, dst = smem + slot * kSlotA;
    const int k0 = (s & 15) * 64;
    mbar_wait(smem + kBarEmptyA + 8 * slot, phase);
    mbar_expect(full, s < 16 ? 32768 : s < 32 ? 40960 : 49152);
    if (s >= 16) mbar_arrive(full);
    tma2(dst, &maps.x, k0, rb * 128, full);
    if (s < 16) {
      tma3(dst + 16384, &maps.wq, k0, cb * 2, full);
    } else if (s < 32) {
      tma3(dst + 16384, &maps.w1a, k0, cb * 7, full);
    } else {
      tma3(dst + 16384, &maps.w1b, k0, cb * 7 + 3, full);
    }
    if (++slot == kSlotsA) { slot = 0; phase ^= 1; }
  }
  const uint32_t phase_a = phase;
  slot = 0;
  phase = 1;
#pragma unroll 1
  for (int s = 0; s < 72; s++) {
    const uint32_t full = smem + kBarFullB + 8 * slot, dst = smem + slot * kSlotB;
    if (s < 6) {
      if (s != 2 && s != 5) mbar_wait(smem + kBarEmptyA + 8 * (s < 2 ? s : s - 1), phase_a);
    } else {
      mbar_wait(smem + kBarEmptyB + 8 * slot, phase);
    }
    mbar_expect(full, 32768);
    if (s < 56) {
      const int t = s - 24;
      const int chunk = s < 24 ? (s / 3) * 7 + s % 3 : (t >> 2) * 7 + 3 + (t & 3);
      tma3(dst + 16384, &maps.w2, chunk * 64, cb * 2, full);
      if (s == 0) flag_wait(g_flag + kFlagHa + rb * 32, 8);
      if (s == 24) flag_wait(g_flag + kFlagHb + rb * 32, 8);
      bulk_load(dst, g_h + (size_t)(rb * 56 + s) * 16384, 16384, full);
    } else {
      const int t = s - 56;
      tma5(dst + 16384, &maps.wo, (t & 3) * 2, t >> 2, cb * 2, full);
      if ((t & 3) == 0) flag_wait(g_flag + kFlagO + (rb * 4 + (t >> 2)) * 32, 8);
      bulk_load(dst, g_o + (size_t)(rb * 16 + t) * 16384, 16384, full);
    }
    if (++slot == kSlotsB) { slot = 0; phase ^= 1; }
  }
  if (atomicAdd(g_flag + kFlagDone, 1) == kCtas - 1) {
    for (int i = 0; i < kFlagWords; i += 32) g_flag[i] = 0;
  }
}

__device__ __forceinline__ void kv_producer(uint32_t smem) {
  flag_wait(g_flag + kFlagKv, X_KVCOUNT);
  mbar_arrive(smem + kBarSeen);
  uint32_t slot = 0, phase = 1;
#pragma unroll 1
  for (int it = 0; it <= 128; it++) {
    const uint32_t full = smem + kBarFullK + 8 * slot;
    mbar_wait(smem + kBarEmptyK + 8 * slot, phase);
    mbar_expect(full, kSlotK);
    bulk_load(smem + kOffKv + slot * kSlotK, g_kv + (it & 31) * kSlotK, kSlotK, full);
    if (++slot == kSlotsK) { slot = 0; phase ^= 1; }
  }
}

__device__ __forceinline__ void helper(uint32_t smem, const __nv_bfloat16* wkv, int rb, int lane) {
  const uint8_t* src = reinterpret_cast<const uint8_t*>(wkv) + lane * 64;
  const uint32_t dst = smem + 32768 + lane * 128 + ((lane & 7) << 4);
  const uint32_t park = smem + kOffKv + lane * 16;
#pragma unroll 1
  for (int i = 0; i < 32; i++) {
    const uint32_t d = i < 8 ? dst + (i >> 1) * kSlotA + (i & 1) * 4096 : park + i * 512;
    asm volatile("cp.async.cg.shared.global [%0], [%1], 16;" ::"r"(d), "l"(src + i * 2048) : "memory");
    if (i == 1 || i == 7) asm volatile("cp.async.commit_group;" ::: "memory");
  }
  asm volatile("cp.async.commit_group;" ::: "memory");
#pragma unroll 1
  for (int s = 0; s < 16; s++) {
    if (s == 0) asm volatile("cp.async.wait_group 2;" ::: "memory");
    if (s == 1) asm volatile("cp.async.wait_group 1;" ::: "memory");
    if (s == 4) asm volatile("cp.async.wait_group 0;" ::: "memory");
    if (s >= 4) {
      uint4 v0, v1;
      asm volatile("ld.shared.v4.u32 {%0, %1, %2, %3}, [%4];" : "=r"(v0.x), "=r"(v0.y), "=r"(v0.z), "=r"(v0.w) : "r"(park + s * 1024) : "memory");
      asm volatile("ld.shared.v4.u32 {%0, %1, %2, %3}, [%4];" : "=r"(v1.x), "=r"(v1.y), "=r"(v1.z), "=r"(v1.w) : "r"(park + s * 1024 + 512) : "memory");
      const uint32_t d = dst + (s & 3) * kSlotA;
      mbar_wait(smem + kBarEmptyA + 8 * (s & 3), ((s >> 2) & 1) ^ 1);
      asm volatile("st.shared.v4.u32 [%0], {%1, %2, %3, %4};" ::"r"(d), "r"(v0.x), "r"(v0.y), "r"(v0.z), "r"(v0.w) : "memory");
      asm volatile("st.shared.v4.u32 [%0], {%1, %2, %3, %4};" ::"r"(d + 4096), "r"(v1.x), "r"(v1.y), "r"(v1.z), "r"(v1.w) : "memory");
    }
    asm volatile("fence.proxy.async.shared::cta;" ::: "memory");
    __syncwarp();
    if (lane == 0) mbar_arrive(smem + kBarFullA + 8 * (s & 3));
  }
  mbar_wait(smem + kBarSeen, 0);
  const float st = __uint_as_float(__ldcg(g_flag + kStat + (lane & 7) * 32));
  const float4 gv = __ldcg(reinterpret_cast<const float4*>(g_gate) + rb * 32 + lane);
  asm volatile("st.shared.v4.f32 [%0], {%1, %2, %3, %4};" ::"r"(smem + kOffGate + lane * 16), "f"(gv.x), "f"(gv.y), "f"(gv.z), "f"(gv.w) : "memory");
  const float ks = quad_sum(st);
  float vm = fmaxf(st, __shfl_xor_sync(~0u, st, 1));
  vm = fmaxf(vm, __shfl_xor_sync(~0u, vm, 2));
  vm = __shfl_sync(~0u, vm, 4);
  if (lane == 0) {
    const float bound = (vm >= kMinV && vm <= kMaxV) ? ks : INFINITY;
    asm volatile("st.shared.f32 [%0], %1;" ::"r"(smem + kOffBound), "f"(bound) : "memory");
  }
  __syncwarp();
  if (lane == 0) mbar_arrive(smem + kBarMeta);
}

__device__ __forceinline__ void signaller(uint32_t smem, int rb) {
  const int order[7] = {kEvKv, kEvHa, kEvO, kEvHb, kEvO + 1, kEvO + 2, kEvO + 3};
#pragma unroll
  for (int i = X_SIG == 2; i < 7; i++) {
    const int ev = order[i];
    mbar_wait(smem + kBarEvent + 8 * ev, 0);
    flag_signal(g_flag + (ev == kEvKv ? kFlagKv : ev == kEvHa ? kFlagHa + rb * 32 : ev == kEvHb ? kFlagHb + rb * 32 : kFlagO + (rb * 4 + ev - kEvO) * 32));
  }
}

__global__ void __launch_bounds__(kThreads, 1)
fused_kernel(const __grid_constant__ Maps maps, const __nv_bfloat16* __restrict__ x, const __nv_bfloat16* __restrict__ wk,
             const __nv_bfloat16* __restrict__ wv, const __nv_bfloat16* __restrict__ gate_w) {
  extern __shared__ __align__(1024) uint8_t smem_raw[];
  const uint32_t smem = __shfl_sync(~0u, ((uint32_t)__cvta_generic_to_shared(smem_raw) + 1023) & ~1023u, 0);
  const int warp = __shfl_sync(~0u, threadIdx.x >> 5, 0);
  const int rb = blockIdx.x & 15, cb = blockIdx.x >> 4;
  if (threadIdx.x == 256) {
    for (int s = 0; s < kSlotsA; s++) { mbar_init(smem + kBarFullA + 8 * s, 2); mbar_init(smem + kBarEmptyA + 8 * s, 2); }
    for (int s = 0; s < kSlotsB; s++) { mbar_init(smem + kBarFullB + 8 * s, 1); mbar_init(smem + kBarEmptyB + 8 * s, 2); }
    for (int s = 0; s < kSlotsK; s++) { mbar_init(smem + kBarFullK + 8 * s, 1); mbar_init(smem + kBarEmptyK + 8 * s, 2); }
    for (int s = 0; s < 7; s++) mbar_init(smem + kBarEvent + 8 * s, 8);
    mbar_init(smem + kBarMeta, 1);
    mbar_init(smem + kBarSeen, 1);
    asm volatile("fence.mbarrier_init.release.cluster;" ::: "memory");
    prefetch_map(&maps.x);
    prefetch_map(&maps.wq);
  }
  __syncthreads();
  if (warp >= 8) {
    asm volatile("setmaxnreg.dec.sync.aligned.u32 24;");
    if (warp == 8) {
      if (elect_one()) gemm_producer(maps, smem, rb, cb);
    } else if (warp == 9) {
      if (elect_one()) kv_producer(smem);
    } else if (warp == 10) {
      if (elect_one()) signaller(smem, rb);
    } else {
      helper(smem, (cb < 4 ? wk : wv) + (cb & 3) * 8, rb, threadIdx.x & 31);
    }
  } else {
    asm volatile("setmaxnreg.inc.sync.aligned.u32 240;");
    const Ctx c{smem, warp >> 2, warp & 3, (int)(threadIdx.x & 31), rb, cb, (threadIdx.x & 127) == 0};
    consumer(maps, c, x, gate_w);
  }
}

using EncodeFn = CUresult (*)(CUtensorMap*, CUtensorMapDataType, cuuint32_t, void*, const cuuint64_t*, const cuuint64_t*,
                              const cuuint32_t*, const cuuint32_t*, CUtensorMapInterleave, CUtensorMapSwizzle,
                              CUtensorMapL2promotion, CUtensorMapFloatOOBfill);

void encode(EncodeFn fn, CUtensorMap* map, const void* base, int rank, const cuuint64_t* dims, const cuuint64_t* strides,
            const cuuint32_t* box) {
  const cuuint32_t ones[5] = {1, 1, 1, 1, 1};
  fn(map, CU_TENSOR_MAP_DATA_TYPE_BFLOAT16, rank, const_cast<void*>(base), dims, strides, box, ones, CU_TENSOR_MAP_INTERLEAVE_NONE,
     CU_TENSOR_MAP_SWIZZLE_128B, CU_TENSOR_MAP_L2_PROMOTION_L2_128B, CU_TENSOR_MAP_FLOAT_OOB_FILL_NONE);
}
void encode_chunked(EncodeFn fn, CUtensorMap* map, const void* base, int rows, int cols, int chunks) {
  const cuuint64_t dims[3] = {64, (cuuint64_t)rows, (cuuint64_t)cols / 64};
  const cuuint64_t strides[2] = {(cuuint64_t)cols * 2, 128};
  const cuuint32_t box[3] = {64, 64, (cuuint32_t)chunks};
  encode(fn, map, base, 3, dims, strides, box);
}
void encode_plain(EncodeFn fn, CUtensorMap* map, const void* base, int rows, int cols, int box_rows) {
  const cuuint64_t dims[2] = {(cuuint64_t)cols, (cuuint64_t)rows};
  const cuuint64_t strides[1] = {(cuuint64_t)cols * 2};
  const cuuint32_t box[2] = {64, (cuuint32_t)box_rows};
  encode(fn, map, base, 2, dims, strides, box);
}

}

extern "C" void kernel_launch(void* const* d_in, const int* in_sizes, int n_in, void* d_out, int out_size) {
  (void)in_sizes; (void)n_in; (void)out_size;
  void* fn_ptr = nullptr;
  cudaDriverEntryPointQueryResult status;
  cudaGetDriverEntryPoint("cuTensorMapEncodeTiled", &fn_ptr, cudaEnableDefault, &status);
  const EncodeFn fn = reinterpret_cast<EncodeFn>(fn_ptr);
  Maps maps;
  encode_plain(fn, &maps.x, d_in[0], 2048, 1024, 128);
  encode_chunked(fn, &maps.wq, d_in[1], 1024, 1024, 2);
  encode_chunked(fn, &maps.w1a, d_in[6], 1024, 3584, 3);
  encode_chunked(fn, &maps.w1b, d_in[6], 1024, 3584, 4);
  encode_chunked(fn, &maps.w2, d_in[7], 3584, 1024, 2);
  {
    const cuuint64_t dims[5] = {64, 32, 8, 4, 16};
    const cuuint64_t strides[4] = {2048, 128 * 2048, 32 * 2048, 128};
    const cuuint32_t box[5] = {64, 32, 2, 1, 2};
    encode(fn, &maps.wo, d_in[4], 5, dims, strides, box);
  }
  encode_chunked(fn, &maps.out, d_out, 2048, 1024, 2);
  cudaFuncSetAttribute(fused_kernel, cudaFuncAttributeMaxDynamicSharedMemorySize, kSmemBytes);
  fused_kernel<<<kCtas, kThreads, kSmemBytes>>>(
      maps, static_cast<const __nv_bfloat16*>(d_in[0]), static_cast<const __nv_bfloat16*>(d_in[2]),
      static_cast<const __nv_bfloat16*>(d_in[3]), static_cast<const __nv_bfloat16*>(d_in[8]));
}
```

```cpp
#include <cuda.h>
#include <cuda_bf16.h>
#include <cuda_runtime.h>
#include <stdint.h>

namespace {

constexpr int kCtas = 128;
constexpr int kThreads = 384;

constexpr int kPureHead = 4;
constexpr int kPureTail = 6;
constexpr int kItA = (16 - kPureHead) * 2;
constexpr int kItB = 32;
constexpr int kDouble = 128 - kItA - kItB - (68 - kPureTail);
constexpr int kItDouble = kItA + kItB + 2 * kDouble;
static_assert(kItA < 31 && kItA + kItB > 33 && kItA + kItB < 64, "no row-tile boundary inside the n192 tile");
static_assert(kDouble > 0 && kDouble + kPureTail <= 68 && kPureTail <= 12 && kDouble < 56, "bad schedule");

constexpr uint32_t kSmem = 1024;
constexpr uint32_t kSlotA = 49152, kSlotsA = 4;
constexpr uint32_t kSlotB = 32768, kSlotsB = 6;
constexpr uint32_t kSlotK = 8192, kSlotsK = 4;
constexpr uint32_t kOffKv = kSlotA * kSlotsA;
constexpr uint32_t kOffMisc = kOffKv + kSlotK * kSlotsK;
constexpr uint32_t kBarFullA = kOffMisc, kBarEmptyA = kBarFullA + 8 * kSlotsA;
constexpr uint32_t kSlotsRaw = 4, kOffRaw = kOffKv + 4096, kBarRaw = kBarEmptyA + 8 * kSlotsA;
constexpr uint32_t kBarFullB = kBarRaw + 8 * kSlotsRaw, kBarEmptyB = kBarFullB + 8 * kSlotsB;
constexpr uint32_t kBarFullK = kBarEmptyB + 8 * kSlotsB, kBarEmptyK = kBarFullK + 8 * kSlotsK;
enum { kEvKv = 0, kEvHa = 1, kEvHb = 4, kEvO = 8, kEvGate = 12, kEvents = 13 };
constexpr uint32_t kBarEvent = kBarEmptyK + 8 * kSlotsK;
constexpr uint32_t kBarDrained = kBarEvent + 8 * kEvents;
constexpr uint32_t kBarDummy = kBarDrained + 16;
constexpr uint32_t kBarMeta = kBarDummy + 8;
constexpr uint32_t kBarGate = kBarMeta + 8;
constexpr uint32_t kOffBound = kBarGate + 8;
constexpr uint32_t kOffQmax = kOffMisc + 544;
constexpr uint32_t kOffStat = kOffMisc + 576;
constexpr uint32_t kOffGate = kOffMisc + 608;
constexpr uint32_t kSmemBytes = kOffGate + 512;
constexpr uint32_t kStageHa = 3 * kSlotA, kStageHb = 4 * kSlotB;
static_assert(71 % kSlotsB >= 3, "the last four stages must not wrap");
static_assert(kOffBound + 4 <= kOffQmax, "misc area overflow");

constexpr int kFlagDone = 0, kFlagKv = 32, kFlagHa = 64, kFlagHb = kFlagHa + 16 * 32, kFlagO = kFlagHb + 16 * 32;
constexpr int kFlagGate = kFlagO + 64 * 32, kFlagWords = kFlagGate + 16 * 32;
__device__ __align__(1024) uint8_t g_img[16 * 72 * 16384];
__device__ __align__(1024) uint8_t g_kv[32 * 8192];
__device__ __align__(1024) uint4 g_q[kCtas * 4 * 2 * 256];
__device__ __align__(1024) float g_gate[2048];
__device__ __align__(1024) unsigned g_flag[kFlagWords];

struct Weights {
  const __nv_bfloat16 *wk, *wv, *gate;
};
struct Maps {
  CUtensorMap x, wq, w1a, w1b, w2, wo, out;
};

constexpr float kScale = 0.25503487f;
constexpr float kMaxScore = 80.f;
constexpr float kMinV = 2.3841858e-07f, kMaxV = 1073741824.f;

__device__ __forceinline__ void mbar_init(uint32_t bar, uint32_t count) {
  asm volatile("mbarrier.init.shared::cta.b64 [%0], %1;" ::"r"(bar), "r"(count));
}
__device__ __forceinline__ void mbar_expect(uint32_t bar, uint32_t bytes) {
  asm volatile("mbarrier.arrive.expect_tx.shared::cta.b64 _, [%0], %1;" ::"r"(bar), "r"(bytes) : "memory");
}
__device__ __forceinline__ void mbar_arrive(uint32_t bar) {
  asm volatile("mbarrier.arrive.shared::cta.b64 _, [%0];" ::"r"(bar) : "memory");
}
__device__ __forceinline__ void mbar_wait(uint32_t bar, uint32_t parity) {
  asm volatile(
      "{\n.reg .pred p;\n.reg .u32 c;\nmov.u32 c, 0;\n"
      "LOOP:\nmbarrier.try_wait.parity.shared::cta.b64 p, [%0], %1;\n@p bra DONE;\n"
      "add.u32 c, c, 1;\nsetp.lt.u32 p, c, 0x80000;\n@p bra LOOP;\nDONE:\n}\n" ::"r"(bar), "r"(parity)
      : "memory");
}
__device__ __forceinline__ bool mbar_try(uint32_t bar, uint32_t parity) {
  uint32_t ok;
  asm volatile("{\n.reg .pred p;\nmbarrier.test_wait.parity.shared::cta.b64 p, [%1], %2;\nselp.u32 %0, 1, 0, p;\n}\n"
               : "=r"(ok) : "r"(bar), "r"(parity) : "memory");
  return ok;
}
__device__ __forceinline__ void flag_wait(const unsigned* flag, unsigned target) {
  asm volatile(
      "{\n.reg .pred p;\n.reg .u32 c, v;\nmov.u32 c, 0;\n"
      "LOOP:\nld.relaxed.gpu.global.u32 v, [%0];\nsetp.ge.u32 p, v, %1;\n@p bra DONE;\n"
      "add.u32 c, c, 1;\nsetp.lt.u32 p, c, 0x20000;\n@p bra LOOP;\n"
      "DONE:\nfence.acquire.gpu;\nfence.proxy.async.global;\n}\n" ::"l"(flag), "r"(target)
      : "memory");
}
__device__ __forceinline__ void flag_signal(unsigned* flag) {
  asm volatile("red.release.gpu.global.add.u32 [%0], 1;" ::"l"(flag) : "memory");
}
__device__ __forceinline__ bool elect_one() {
  uint32_t p;
  asm volatile("{\n.reg .pred P;\nelect.sync _|P, 0xffffffff;\nselp.u32 %0, 1, 0, P;\n}\n" : "=r"(p));
  return p;
}
__device__ __forceinline__ void bulk_load(uint32_t dst, const void* src, uint32_t bytes, uint32_t bar) {
  asm volatile("cp.async.bulk.shared::cluster.global.mbarrier::complete_tx::bytes [%0], [%1], %2, [%3];" ::"r"(dst),
               "l"(src), "r"(bytes), "r"(bar)
               : "memory");
}
__device__ __forceinline__ void bulk_store(void* dst, uint32_t src, uint32_t bytes) {
  asm volatile("cp.async.bulk.global.shared::cta.bulk_group [%0], [%1], %2;" ::"l"(dst), "r"(src), "r"(bytes) : "memory");
}
__device__ __forceinline__ void tma2(uint32_t dst, const CUtensorMap* m, int c0, int c1, uint32_t bar) {
  asm volatile("cp.async.bulk.tensor.2d.shared::cluster.global.mbarrier::complete_tx::bytes [%0], [%1, {%3, %4}], [%2];" ::"r"(dst),
               "l"(m), "r"(bar), "r"(c0), "r"(c1)
               : "memory");
}
__device__ __forceinline__ uint64_t policy_evict_first() {
  uint64_t p;
  asm("createpolicy.fractional.L2::evict_first.b64 %0, 1.0;" : "=l"(p));
  return p;
}
__device__ __forceinline__ void tma3(uint32_t dst, const CUtensorMap* m, int c1, int c2, uint32_t bar, uint64_t policy) {
  asm volatile("cp.async.bulk.tensor.3d.shared::cluster.global.mbarrier::complete_tx::bytes.L2::cache_hint [%0], [%1, {0, %3, %4}], [%2], %5;" ::"r"(dst),
               "l"(m), "r"(bar), "r"(c1), "r"(c2), "l"(policy)
               : "memory");
}
__device__ __forceinline__ void tma5(uint32_t dst, const CUtensorMap* m, int c2, int c3, int c4, uint32_t bar, uint64_t policy) {
  asm volatile("cp.async.bulk.tensor.5d.shared::cluster.global.mbarrier::complete_tx::bytes.L2::cache_hint [%0], [%1, {0, 0, %3, %4, %5}], [%2], %6;" ::"r"(dst),
               "l"(m), "r"(bar), "r"(c2), "r"(c3), "r"(c4), "l"(policy)
               : "memory");
}
__device__ __forceinline__ void tma3_store(const CUtensorMap* m, uint32_t src, int c1, int c2) {
  asm volatile("cp.async.bulk.tensor.3d.global.shared::cta.bulk_group [%0, {0, %2, %3}], [%1];" ::"l"(m), "r"(src), "r"(c1), "r"(c2)
               : "memory");
}
__device__ __forceinline__ void wg_fence() { asm volatile("wgmma.fence.sync.aligned;" ::: "memory"); }
__device__ __forceinline__ void wg_commit() { asm volatile("wgmma.commit_group.sync.aligned;" ::: "memory"); }
template <int N>
__device__ __forceinline__ void wg_wait() { asm volatile("wgmma.wait_group.sync.aligned %0;" ::"n"(N) : "memory"); }
template <int R>
__device__ __forceinline__ void pin(float (&a)[R]) {
#pragma unroll
  for (int i = 0; i < R; i++) asm volatile("" : "+f"(a[i])::"memory");
}
__host__ __device__ constexpr uint64_t make_desc(uint32_t addr, uint32_t lbo, uint32_t sbo, uint32_t swizzle) {
  return (uint64_t)((addr & 0x3FFFF) >> 4) | ((uint64_t)(lbo >> 4) << 16) | ((uint64_t)(sbo >> 4) << 32) | ((uint64_t)swizzle << 62);
}
__device__ __forceinline__ float ex2(float x) {
  float y;
  asm("ex2.approx.ftz.f32 %0, %1;" : "=f"(y) : "f"(x));
  return y;
}
__device__ __forceinline__ float rcp(float x) {
  float y;
  asm("rcp.approx.ftz.f32 %0, %1;" : "=f"(y) : "f"(x));
  return y;
}
__device__ __forceinline__ float sigmoid(float x) { return rcp(1.f + ex2(x * -1.4426950408889634f)); }
__device__ __forceinline__ uint32_t pack2(float lo, float hi) {
  uint32_t r;
  asm("cvt.rn.bf16x2.f32 %0, %1, %2;" : "=r"(r) : "f"(hi), "f"(lo));
  return r;
}
__device__ __forceinline__ float bf_lo(uint32_t v) { return __uint_as_float(v << 16); }
__device__ __forceinline__ float bf_hi(uint32_t v) { return __uint_as_float(v & 0xffff0000u); }
__device__ __forceinline__ float lds_f32(uint32_t addr) {
  float v;
  asm volatile("ld.shared.f32 %0, [%1];" : "=f"(v) : "r"(addr) : "memory");
  return v;
}
__device__ __forceinline__ uint32_t lds_u32(uint32_t addr) {
  uint32_t v;
  asm volatile("ld.shared.u32 %0, [%1];" : "=r"(v) : "r"(addr) : "memory");
  return v;
}
__device__ __forceinline__ float quad_sum(float v) {
  v += __shfl_xor_sync(~0u, v, 1);
  return v + __shfl_xor_sync(~0u, v, 2);
}

__device__ __forceinline__ void wgmma_rs_n32(float (&d)[16], const uint32_t (&a)[4], uint64_t db, int accumulate) {
  asm volatile(
      "{\n.reg .pred p;\nsetp.ne.b32 p, %21, 0;\n"
      "wgmma.mma_async.sync.aligned.m64n32k16.f32.bf16.bf16 {"
      "%0, %1, %2, %3, %4, %5, %6, %7, %8, %9, %10, %11, %12, %13, %14, %15"
      "}, {%16, %17, %18, %19}, %20, p, 1, 1, 1;\n}\n"
      : "+f"(d[0]), "+f"(d[1]), "+f"(d[2]), "+f"(d[3]), "+f"(d[4]), "+f"(d[5]), "+f"(d[6]), "+f"(d[7]),
        "+f"(d[8]), "+f"(d[9]), "+f"(d[10]), "+f"(d[11]), "+f"(d[12]), "+f"(d[13]), "+f"(d[14]), "+f"(d[15])
      : "r"(a[0]), "r"(a[1]), "r"(a[2]), "r"(a[3]), "l"(db), "r"(accumulate));
}
__device__ __forceinline__ void wgmma_rs_n64(float (&d)[32], const uint32_t (&a)[4], uint64_t db, int accumulate) {
  asm volatile(
      "{\n.reg .pred p;\nsetp.ne.b32 p, %37, 0;\n"
      "wgmma.mma_async.sync.aligned.m64n64k16.f32.bf16.bf16 {"
      "%0, %1, %2, %3, %4, %5, %6, %7, %8, %9, %10, %11, %12, %13, %14, %15, "
      "%16, %17, %18, %19, %20, %21, %22, %23, %24, %25, %26, %27, %28, %29, %30, %31"
      "}, {%32, %33, %34, %35}, %36, p, 1, 1, 0;\n}\n"
      : "+f"(d[0]), "+f"(d[1]), "+f"(d[2]), "+f"(d[3]), "+f"(d[4]), "+f"(d[5]), "+f"(d[6]), "+f"(d[7]),
        "+f"(d[8]), "+f"(d[9]), "+f"(d[10]), "+f"(d[11]), "+f"(d[12]), "+f"(d[13]), "+f"(d[14]), "+f"(d[15]),
        "+f"(d[16]), "+f"(d[17]), "+f"(d[18]), "+f"(d[19]), "+f"(d[20]), "+f"(d[21]), "+f"(d[22]), "+f"(d[23]),
        "+f"(d[24]), "+f"(d[25]), "+f"(d[26]), "+f"(d[27]), "+f"(d[28]), "+f"(d[29]), "+f"(d[30]), "+f"(d[31])
      : "r"(a[0]), "r"(a[1]), "r"(a[2]), "r"(a[3]), "l"(db), "r"(accumulate));
}
__device__ __forceinline__ void wgmma_ss(float (&d)[64], uint64_t da, uint64_t db, int accumulate) {
  asm volatile(
      "{\n.reg .pred p;\nsetp.ne.b32 p, %66, 0;\n"
      "wgmma.mma_async.sync.aligned.m64n128k16.f32.bf16.bf16 {"
      "%0, %1, %2, %3, %4, %5, %6, %7, %8, %9, %10, %11, %12, %13, %14, %15, "
      "%16, %17, %18, %19, %20, %21, %22, %23, %24, %25, %26, %27, %28, %29, %30, %31, "
      "%32, %33, %34, %35, %36, %37, %38, %39, %40, %41, %42, %43, %44, %45, %46, %47, "
      "%48, %49, %50, %51, %52, %53, %54, %55, %56, %57, %58, %59, %60, %61, %62, %63"
      "}, %64, %65, p, 1, 1, 0, 1;\n}\n"
      : "+f"(d[0]), "+f"(d[1]), "+f"(d[2]), "+f"(d[3]), "+f"(d[4]), "+f"(d[5]), "+f"(d[6]), "+f"(d[7]),
        "+f"(d[8]), "+f"(d[9]), "+f"(d[10]), "+f"(d[11]), "+f"(d[12]), "+f"(d[13]), "+f"(d[14]), "+f"(d[15]),
        "+f"(d[16]), "+f"(d[17]), "+f"(d[18]), "+f"(d[19]), "+f"(d[20]), "+f"(d[21]), "+f"(d[22]), "+f"(d[23]),
        "+f"(d[24]), "+f"(d[25]), "+f"(d[26]), "+f"(d[27]), "+f"(d[28]), "+f"(d[29]), "+f"(d[30]), "+f"(d[31]),
        "+f"(d[32]), "+f"(d[33]), "+f"(d[34]), "+f"(d[35]), "+f"(d[36]), "+f"(d[37]), "+f"(d[38]), "+f"(d[39]),
        "+f"(d[40]), "+f"(d[41]), "+f"(d[42]), "+f"(d[43]), "+f"(d[44]), "+f"(d[45]), "+f"(d[46]), "+f"(d[47]),
        "+f"(d[48]), "+f"(d[49]), "+f"(d[50]), "+f"(d[51]), "+f"(d[52]), "+f"(d[53]), "+f"(d[54]), "+f"(d[55]),
        "+f"(d[56]), "+f"(d[57]), "+f"(d[58]), "+f"(d[59]), "+f"(d[60]), "+f"(d[61]), "+f"(d[62]), "+f"(d[63])
      : "l"(da), "l"(db), "r"(accumulate));
}
__device__ __forceinline__ void wgmma_ss(float (&d)[68], uint64_t da, uint64_t db, int accumulate) {
  asm volatile(
      "{\n.reg .pred p;\nsetp.ne.b32 p, %70, 0;\n"
      "wgmma.mma_async.sync.aligned.m64n136k16.f32.bf16.bf16 {"
      "%0, %1, %2, %3, %4, %5, %6, %7, %8, %9, %10, %11, %12, %13, %14, %15, "
      "%16, %17, %18, %19, %20, %21, %22, %23, %24, %25, %26, %27, %28, %29, %30, %31, "
      "%32, %33, %34, %35, %36, %37, %38, %39, %40, %41, %42, %43, %44, %45, %46, %47, "
      "%48, %49, %50, %51, %52, %53, %54, %55, %56, %57, %58, %59, %60, %61, %62, %63, "
      "%64, %65, %66, %67"
      "}, %68, %69, p, 1, 1, 0, 1;\n}\n"
      : "+f"(d[0]), "+f"(d[1]), "+f"(d[2]), "+f"(d[3]), "+f"(d[4]), "+f"(d[5]), "+f"(d[6]), "+f"(d[7]),
        "+f"(d[8]), "+f"(d[9]), "+f"(d[10]), "+f"(d[11]), "+f"(d[12]), "+f"(d[13]), "+f"(d[14]), "+f"(d[15]),
        "+f"(d[16]), "+f"(d[17]), "+f"(d[18]), "+f"(d[19]), "+f"(d[20]), "+f"(d[21]), "+f"(d[22]), "+f"(d[23]),
        "+f"(d[24]), "+f"(d[25]), "+f"(d[26]), "+f"(d[27]), "+f"(d[28]), "+f"(d[29]), "+f"(d[30]), "+f"(d[31]),
        "+f"(d[32]), "+f"(d[33]), "+f"(d[34]), "+f"(d[35]), "+f"(d[36]), "+f"(d[37]), "+f"(d[38]), "+f"(d[39]),
        "+f"(d[40]), "+f"(d[41]), "+f"(d[42]), "+f"(d[43]), "+f"(d[44]), "+f"(d[45]), "+f"(d[46]), "+f"(d[47]),
        "+f"(d[48]), "+f"(d[49]), "+f"(d[50]), "+f"(d[51]), "+f"(d[52]), "+f"(d[53]), "+f"(d[54]), "+f"(d[55]),
        "+f"(d[56]), "+f"(d[57]), "+f"(d[58]), "+f"(d[59]), "+f"(d[60]), "+f"(d[61]), "+f"(d[62]), "+f"(d[63]),
        "+f"(d[64]), "+f"(d[65]), "+f"(d[66]), "+f"(d[67])
      : "l"(da), "l"(db), "r"(accumulate));
}
__device__ __forceinline__ void wgmma_ss(float (&d)[96], uint64_t da, uint64_t db, int accumulate) {
  asm volatile(
      "{\n.reg .pred p;\nsetp.ne.b32 p, %98, 0;\n"
      "wgmma.mma_async.sync.aligned.m64n192k16.f32.bf16.bf16 {"
      "%0, %1, %2, %3, %4, %5, %6, %7, %8, %9, %10, %11, %12, %13, %14, %15, "
      "%16, %17, %18, %19, %20, %21, %22, %23, %24, %25, %26, %27, %28, %29, %30, %31, "
      "%32, %33, %34, %35, %36, %37, %38, %39, %40, %41, %42, %43, %44, %45, %46, %47, "
      "%48, %49, %50, %51, %52, %53, %54, %55, %56, %57, %58, %59, %60, %61, %62, %63, "
      "%64, %65, %66, %67, %68, %69, %70, %71, %72, %73, %74, %75, %76, %77, %78, %79, "
      "%80, %81, %82, %83, %84, %85, %86, %87, %88, %89, %90, %91, %92, %93, %94, %95"
      "}, %96, %97, p, 1, 1, 0, 1;\n}\n"
      : "+f"(d[0]), "+f"(d[1]), "+f"(d[2]), "+f"(d[3]), "+f"(d[4]), "+f"(d[5]), "+f"(d[6]), "+f"(d[7]),
        "+f"(d[8]), "+f"(d[9]), "+f"(d[10]), "+f"(d[11]), "+f"(d[12]), "+f"(d[13]), "+f"(d[14]), "+f"(d[15]),
        "+f"(d[16]), "+f"(d[17]), "+f"(d[18]), "+f"(d[19]), "+f"(d[20]), "+f"(d[21]), "+f"(d[22]), "+f"(d[23]),
        "+f"(d[24]), "+f"(d[25]), "+f"(d[26]), "+f"(d[27]), "+f"(d[28]), "+f"(d[29]), "+f"(d[30]), "+f"(d[31]),
        "+f"(d[32]), "+f"(d[33]), "+f"(d[34]), "+f"(d[35]), "+f"(d[36]), "+f"(d[37]), "+f"(d[38]), "+f"(d[39]),
        "+f"(d[40]), "+f"(d[41]), "+f"(d[42]), "+f"(d[43]), "+f"(d[44]), "+f"(d[45]), "+f"(d[46]), "+f"(d[47]),
        "+f"(d[48]), "+f"(d[49]), "+f"(d[50]), "+f"(d[51]), "+f"(d[52]), "+f"(d[53]), "+f"(d[54]), "+f"(d[55]),
        "+f"(d[56]), "+f"(d[57]), "+f"(d[58]), "+f"(d[59]), "+f"(d[60]), "+f"(d[61]), "+f"(d[62]), "+f"(d[63]),
        "+f"(d[64]), "+f"(d[65]), "+f"(d[66]), "+f"(d[67]), "+f"(d[68]), "+f"(d[69]), "+f"(d[70]), "+f"(d[71]),
        "+f"(d[72]), "+f"(d[73]), "+f"(d[74]), "+f"(d[75]), "+f"(d[76]), "+f"(d[77]), "+f"(d[78]), "+f"(d[79]),
        "+f"(d[80]), "+f"(d[81]), "+f"(d[82]), "+f"(d[83]), "+f"(d[84]), "+f"(d[85]), "+f"(d[86]), "+f"(d[87]),
        "+f"(d[88]), "+f"(d[89]), "+f"(d[90]), "+f"(d[91]), "+f"(d[92]), "+f"(d[93]), "+f"(d[94]), "+f"(d[95])
      : "l"(da), "l"(db), "r"(accumulate));
}
__device__ __forceinline__ void wgmma_ss(float (&d)[128], uint64_t da, uint64_t db, int accumulate) {
  asm volatile(
      "{\n.reg .pred p;\nsetp.ne.b32 p, %130, 0;\n"
      "wgmma.mma_async.sync.aligned.m64n256k16.f32.bf16.bf16 {"
      "%0, %1, %2, %3, %4, %5, %6, %7, %8, %9, %10, %11, %12, %13, %14, %15, "
      "%16, %17, %18, %19, %20, %21, %22, %23, %24, %25, %26, %27, %28, %29, %30, %31, "
      "%32, %33, %34, %35, %36, %37, %38, %39, %40, %41, %42, %43, %44, %45, %46, %47, "
      "%48, %49, %50, %51, %52, %53, %54, %55, %56, %57, %58, %59, %60, %61, %62, %63, "
      "%64, %65, %66, %67, %68, %69, %70, %71, %72, %73, %74, %75, %76, %77, %78, %79, "
      "%80, %81, %82, %83, %84, %85, %86, %87, %88, %89, %90, %91, %92, %93, %94, %95, "
      "%96, %97, %98, %99, %100, %101, %102, %103, %104, %105, %106, %107, %108, %109, %110, %111, "
      "%112, %113, %114, %115, %116, %117, %118, %119, %120, %121, %122, %123, %124, %125, %126, %127"
      "}, %128, %129, p, 1, 1, 0, 1;\n}\n"
      : "+f"(d[0]), "+f"(d[1]), "+f"(d[2]), "+f"(d[3]), "+f"(d[4]), "+f"(d[5]), "+f"(d[6]), "+f"(d[7]),
        "+f"(d[8]), "+f"(d[9]), "+f"(d[10]), "+f"(d[11]), "+f"(d[12]), "+f"(d[13]), "+f"(d[14]), "+f"(d[15]),
        "+f"(d[16]), "+f"(d[17]), "+f"(d[18]), "+f"(d[19]), "+f"(d[20]), "+f"(d[21]), "+f"(d[22]), "+f"(d[23]),
        "+f"(d[24]), "+f"(d[25]), "+f"(d[26]), "+f"(d[27]), "+f"(d[28]), "+f"(d[29]), "+f"(d[30]), "+f"(d[31]),
        "+f"(d[32]), "+f"(d[33]), "+f"(d[34]), "+f"(d[35]), "+f"(d[36]), "+f"(d[37]), "+f"(d[38]), "+f"(d[39]),
        "+f"(d[40]), "+f"(d[41]), "+f"(d[42]), "+f"(d[43]), "+f"(d[44]), "+f"(d[45]), "+f"(d[46]), "+f"(d[47]),
        "+f"(d[48]), "+f"(d[49]), "+f"(d[50]), "+f"(d[51]), "+f"(d[52]), "+f"(d[53]), "+f"(d[54]), "+f"(d[55]),
        "+f"(d[56]), "+f"(d[57]), "+f"(d[58]), "+f"(d[59]), "+f"(d[60]), "+f"(d[61]), "+f"(d[62]), "+f"(d[63]),
        "+f"(d[64]), "+f"(d[65]), "+f"(d[66]), "+f"(d[67]), "+f"(d[68]), "+f"(d[69]), "+f"(d[70]), "+f"(d[71]),
        "+f"(d[72]), "+f"(d[73]), "+f"(d[74]), "+f"(d[75]), "+f"(d[76]), "+f"(d[77]), "+f"(d[78]), "+f"(d[79]),
        "+f"(d[80]), "+f"(d[81]), "+f"(d[82]), "+f"(d[83]), "+f"(d[84]), "+f"(d[85]), "+f"(d[86]), "+f"(d[87]),
        "+f"(d[88]), "+f"(d[89]), "+f"(d[90]), "+f"(d[91]), "+f"(d[92]), "+f"(d[93]), "+f"(d[94]), "+f"(d[95]),
        "+f"(d[96]), "+f"(d[97]), "+f"(d[98]), "+f"(d[99]), "+f"(d[100]), "+f"(d[101]), "+f"(d[102]), "+f"(d[103]),
        "+f"(d[104]), "+f"(d[105]), "+f"(d[106]), "+f"(d[107]), "+f"(d[108]), "+f"(d[109]), "+f"(d[110]), "+f"(d[111]),
        "+f"(d[112]), "+f"(d[113]), "+f"(d[114]), "+f"(d[115]), "+f"(d[116]), "+f"(d[117]), "+f"(d[118]), "+f"(d[119]),
        "+f"(d[120]), "+f"(d[121]), "+f"(d[122]), "+f"(d[123]), "+f"(d[124]), "+f"(d[125]), "+f"(d[126]), "+f"(d[127])
      : "l"(da), "l"(db), "r"(accumulate));
}

struct Ring {
  uint64_t da, db;
  uint32_t slot, phase;
  uint32_t prev;
};
struct Attn {
  float S[32], O[16];
  uint32_t P[4][4], Q[2][4];
  float l0, l1, m0, m1;
  float t0, t1;
  uint64_t dk, dv;
  int it;
  int rare;
};
struct Ctx {
  int wg, warp, lane, rb, cb;
  bool leader;
};

template <bool B> struct RingCfg;
template <> struct RingCfg<false> { static constexpr uint32_t size = kSlotA, slots = kSlotsA, full = kSmem + kBarFullA; };
template <> struct RingCfg<true> { static constexpr uint32_t size = kSlotB, slots = kSlotsB, full = kSmem + kBarFullB; };

__device__ __forceinline__ uint64_t opaque(uint64_t v) {
  asm volatile("" : "+l"(v));
  return v;
}
template <bool B>
__device__ __forceinline__ void ring_reset(const Ctx& c, Ring& r) {
  r.da = opaque((B ? make_desc(kSmem, 128, 1024, 0) : make_desc(kSmem, 16, 1024, 1)) + c.wg * 512);
  r.db = opaque(make_desc(kSmem + 16384, 8192, 1024, 1));
  r.slot = 0;
  r.phase = 0;
  r.prev = kSmem + kBarDummy;
}
__device__ __forceinline__ void ring_release_prev(const Ctx& c, const Ring& r) {
  if (c.leader) mbar_arrive(r.prev);
}
template <bool B>
__device__ __forceinline__ uint32_t ring_full(const Ring& r) { return RingCfg<B>::full + 8 * r.slot; }
template <bool B>
__device__ __forceinline__ void ring_advance(Ring& r) {
  r.prev = ring_full<B>(r) + 8 * RingCfg<B>::slots;
  const uint32_t old = r.slot;
  if (++r.slot == RingCfg<B>::slots) { r.slot = 0; r.phase ^= 1; }
  if (B) {
    const uint64_t flip = (old ^ r.slot) * (kSlotB >> 4);
    r.da ^= flip;
    r.db ^= flip;
  } else {
    const uint32_t step = (r.slot - old) * (kSlotA >> 4);
    r.da ^= (uint32_t)r.da ^ ((uint32_t)r.da + step);
    r.db ^= (uint32_t)r.db ^ ((uint32_t)r.db + step);
  }
}
template <bool B, int K0, int K1, int R>
__device__ __forceinline__ void gemm_steps(float (&acc)[R], const Ring& r, int accumulate) {
#pragma unroll
  for (int k = K0; k < K1; k++) wgmma_ss(acc, r.da + k * (B ? 16 : 2), r.db + k * 128, k == 0 ? accumulate : 1);
}
template <bool B, int R>
__device__ __forceinline__ void stage_pure(const Ctx& c, Ring& r, float (&acc)[R], int accumulate) {
  mbar_wait(ring_full<B>(r), r.phase);
  wg_fence();
  gemm_steps<B, 0, 4>(acc, r, accumulate);
  wg_commit();
  wg_wait<1>();
  ring_release_prev(c, r);
  ring_advance<B>(r);
}
__device__ __forceinline__ void ring_drain(const Ctx& c, Ring& r) {
  wg_wait<0>();
  ring_release_prev(c, r);
  r.prev = kSmem + kBarDummy;
}
__device__ __forceinline__ void event_arrive(const Ctx& c, int ev) {
  __syncwarp();
  if (c.lane == 0) mbar_arrive(kSmem + kBarEvent + 8 * ev);
}
__device__ __forceinline__ uint32_t gate_addr(const Ctx& c) {
  return kSmem + kOffGate + (c.wg * 64 + c.warp * 16 + (c.lane >> 2)) * 4;
}

__device__ __forceinline__ void attn_finish(const Ctx& c, Attn& a, int round) {
  pin(a.O);
  const float s0 = lds_f32(gate_addr(c)) * rcp(quad_sum(a.l0));
  const float s1 = lds_f32(gate_addr(c) + 32) * rcp(quad_sum(a.l1));
  uint8_t* dst = g_img + (size_t)(c.rb * 72 + 56 + round * 4 + (c.cb >> 1)) * 16384 + (c.wg * 8 + c.warp * 2) * 1024 + (c.cb & 1) * 512 + c.lane * 4;
#pragma unroll
  for (int j = 0; j < 4; j++) {
    const uint32_t lo = pack2(a.O[4 * j] * s0, a.O[4 * j + 1] * s0), hi = pack2(a.O[4 * j + 2] * s1, a.O[4 * j + 3] * s1);
    *reinterpret_cast<uint32_t*>(dst + j * 128) = lo;
    *reinterpret_cast<uint32_t*>(dst + j * 128 + 1024) = hi;
  }
  event_arrive(c, kEvO + round);
#pragma unroll
  for (int i = 0; i < 16; i++) a.O[i] = 0.f;
  a.l0 = 0.f;
  a.l1 = 0.f;
}
__device__ __forceinline__ const uint4* q_slot(int head) { return g_q + (blockIdx.x * 4 + head) * 512 + threadIdx.x; }
__device__ __forceinline__ void load_q(uint32_t (&q)[2][4], const uint4* src) {
  const uint4 q0 = __ldcg(src), q1 = __ldcg(src + 256);
  q[0][0] = q0.x; q[0][1] = q0.y; q[0][2] = q0.z; q[0][3] = q0.w;
  q[1][0] = q1.x; q[1][1] = q1.y; q[1][2] = q1.z; q[1][3] = q1.w;
}
__device__ __forceinline__ void attn_pv(Attn& a) {
#pragma unroll
  for (int t = 0; t < 4; t++) wgmma_rs_n32(a.O, a.P[t], a.dv + t * 64, 1);
}

template <bool FAST, bool B, int K0, int K1, int R>
__device__ __forceinline__ bool attn_step(const Ctx& c, Attn& a, Ring& r, float (&acc)[R], int accumulate, const uint4* q_head1) {
  a.l0 += a.t0;
  a.l1 += a.t1;
  wg_fence();
  wgmma_rs_n32(a.O, a.P[0], a.dv, 1);
  wgmma_rs_n64(a.S, a.Q[0], a.dk, 0);
  wgmma_rs_n32(a.O, a.P[1], a.dv + 64, 1);
  wgmma_rs_n64(a.S, a.Q[1], a.dk + 16, 1);
  wg_commit();
  wgmma_rs_n32(a.O, a.P[2], a.dv + 128, 1);
  wgmma_rs_n32(a.O, a.P[3], a.dv + 192, 1);
  wg_commit();
  gemm_steps<B, K0, K1>(acc, r, accumulate);
  wg_commit();
  wg_wait<2>();
  if (K0 == 0) ring_release_prev(c, r);
  if (K1 == 4) ring_advance<B>(r);
  pin(a.S);
  if (R == 128 && K1 == 4 && a.it == 31) load_q(a.Q, q_head1);
  const uint32_t kv_empty = kSmem + kBarEmptyK + 8 * (a.it & 3);
  const uint64_t flip = ((a.it ^ (a.it + 1)) & 3) * (kSlotK >> 4);
  a.dk ^= flip;
  a.dv ^= flip;
  float s0, s1, s2, s3;
  if (FAST) {
    float e[8];
#pragma unroll
    for (int i = 0; i < 8; i++) e[i] = ex2(a.S[i]);
    wg_wait<1>();
    if (c.leader) mbar_arrive(kv_empty);
#pragma unroll
    for (int i = 0; i < 32; i += 4) {
      const float p0 = i < 8 ? e[i] : ex2(a.S[i]), p1 = i < 8 ? e[i + 1] : ex2(a.S[i + 1]);
      const float p2 = i < 8 ? e[i + 2] : ex2(a.S[i + 2]), p3 = i < 8 ? e[i + 3] : ex2(a.S[i + 3]);
      if (i == 0) { s0 = p0; s1 = p1; s2 = p2; s3 = p3; } else { s0 += p0; s1 += p1; s2 += p2; s3 += p3; }
      a.P[i / 8][(i % 8) / 2] = pack2(p0, p1);
      a.P[i / 8][(i % 8) / 2 + 1] = pack2(p2, p3);
    }
  } else {
    wg_wait<1>();
    if (c.leader) mbar_arrive(kv_empty);
    pin(a.O);
    if ((a.it & 31) == 0 && a.it != 0) {
      attn_finish(c, a, (a.it >> 5) - 1);
      a.m0 = -INFINITY;
      a.m1 = -INFINITY;
    }
    float x0 = a.m0, x1 = a.m1;
#pragma unroll
    for (int i = 0; i < 32; i += 4) {
      x0 = fmaxf(x0, fmaxf(a.S[i], a.S[i + 1]));
      x1 = fmaxf(x1, fmaxf(a.S[i + 2], a.S[i + 3]));
    }
    x0 = fmaxf(x0, __shfl_xor_sync(~0u, x0, 1));
    x1 = fmaxf(x1, __shfl_xor_sync(~0u, x1, 1));
    x0 = fmaxf(x0, __shfl_xor_sync(~0u, x0, 2));
    x1 = fmaxf(x1, __shfl_xor_sync(~0u, x1, 2));
    const float a0 = ex2(a.m0 - x0), a1 = ex2(a.m1 - x1);
    a.m0 = x0;
    a.m1 = x1;
    a.l0 *= a0;
    a.l1 *= a1;
#pragma unroll
    for (int i = 0; i < 16; i += 4) { a.O[i] *= a0; a.O[i + 1] *= a0; a.O[i + 2] *= a1; a.O[i + 3] *= a1; }
#pragma unroll
    for (int i = 0; i < 32; i += 4) {
      const float p0 = ex2(a.S[i] - x0), p1 = ex2(a.S[i + 1] - x0), p2 = ex2(a.S[i + 2] - x1), p3 = ex2(a.S[i + 3] - x1);
      if (i == 0) { s0 = p0; s1 = p1; s2 = p2; s3 = p3; } else { s0 += p0; s1 += p1; s2 += p2; s3 += p3; }
      a.P[i / 8][(i % 8) / 2] = pack2(p0, p1);
      a.P[i / 8][(i % 8) / 2 + 1] = pack2(p2, p3);
    }
  }
  a.t0 = s0 + s1;
  a.t1 = s2 + s3;
  a.it++;
  bool ready = mbar_try(kSmem + kBarFullK + 8 * (a.it & 3), a.it >> 2);
  if (K1 == 4) ready &= mbar_try(ring_full<B>(r), r.phase);
  return ready;
}

__host__ __device__ constexpr int next_event(int it, int end) {
  const int e = it < 33 ? 33 : it < 64 ? 64 : it < 65 ? 65 : it < 96 ? 96 : it < 97 ? 97 : 128;
  return e < end ? e : end;
}
template <bool B, bool RING>
__device__ __forceinline__ void wait_operands(const Attn& a, const Ring& r) {
  mbar_wait(kSmem + kBarFullK + 8 * (a.it & 3), (a.it >> 2) & 1);
  if (RING) mbar_wait(ring_full<B>(r), r.phase);
}
template <bool FAST, bool B, int BEGIN, int END, bool EVEN, bool ODD, bool RING>
__device__ __forceinline__ void attn_rare(const Ctx& c, Attn& a, Ring& r, bool ready, uint32_t (&qn)[2][4]) {
  constexpr auto in = [](int e) { return BEGIN < e && e < END; };
  constexpr bool swap = EVEN && (in(64) || in(96)), finish = ODD && (in(33) || in(65) || in(97));
  if ((swap || finish) && a.it == a.rare) {
    if (swap && (!finish || !(a.it & 1))) {
#pragma unroll
      for (int i = 0; i < 8; i++) a.Q[i / 4][i % 4] = qn[i / 4][i % 4];
    } else {
      if (in(65) && a.it == 65) load_q(qn, q_slot(3));
      if (FAST) attn_finish(c, a, (a.it >> 5) - 1);
    }
    a.rare = next_event(a.it, END);
  }
  if (!ready) wait_operands<B, RING>(a, r);
}

template <bool FAST, bool B, int BEGIN, int END, bool FRESH, int R>
__device__ __forceinline__ void run_double(const Ctx& c, Attn& a, Ring& r, float (&acc)[R], uint32_t (&qn)[2][4]) {
  static_assert(BEGIN % 2 == 0 && END % 2 == 0 && next_event(BEGIN - 1, 128) != BEGIN, "bad phase boundary");
  const uint4* q_head1 = R == 128 ? reinterpret_cast<const uint4*>(opaque(reinterpret_cast<uint64_t>(q_slot(1)))) : nullptr;
  a.rare = next_event(BEGIN, END);
  wait_operands<B, true>(a, r);
#pragma unroll 1
  while (true) {
    bool ready;
#pragma unroll 1
    do {
      ready = attn_step<FAST, B, 0, 2>(c, a, r, acc, !FRESH || a.it != BEGIN, q_head1);
      if (!ready || a.it == a.rare) attn_rare<FAST, B, BEGIN, END, false, true, false>(c, a, r, ready, qn);
      ready = attn_step<FAST, B, 2, 4>(c, a, r, acc, 1, q_head1);
    } while (ready && a.it != a.rare);
    if (a.it == END) break;
    attn_rare<FAST, B, BEGIN, END, true, false, true>(c, a, r, ready, qn);
  }
}
template <bool FAST, int BEGIN, int END>
__device__ __forceinline__ void run_single(const Ctx& c, Attn& a, Ring& r, float (&acc)[64], uint32_t (&qn)[2][4]) {
  static_assert(next_event(BEGIN - 1, 128) != BEGIN, "bad phase boundary");
  a.rare = next_event(BEGIN, END);
  wait_operands<true, true>(a, r);
#pragma unroll 1
  while (true) {
    bool ready;
#pragma unroll 1
    do ready = attn_step<FAST, true, 0, 4>(c, a, r, acc, 1, nullptr);
    while (ready && a.it != a.rare);
    if (a.it == END) break;
    attn_rare<FAST, true, BEGIN, END, true, true, true>(c, a, r, ready, qn);
  }
}

__device__ __forceinline__ float scaled_silu(float x, float half_k) {
  float t;
  asm("tanh.approx.f32 %0, %1;" : "=f"(t) : "f"(0.5f * x));
  const float y = x * half_k;
  return fmaf(y, t, y);
}
template <int R>
__device__ __forceinline__ void store_h(const Ctx& c, float (&acc)[R], uint32_t stage, int ev) {
  pin(acc);
  uint32_t dst = kSmem + stage + (c.wg * 8 + c.warp * 2 + ((c.lane >> 3) & 1)) * 1024 + (c.lane >> 4) * 128 + (c.lane & 7) * 16;
  if (R == 96) mbar_wait(kSmem + kBarGate, 0);
  const float k0 = fmaf(lds_f32(gate_addr(c)), -0.5f, 0.5f), k1 = fmaf(lds_f32(gate_addr(c) + 32), -0.5f, 0.5f);
  constexpr int U = R == 96 ? 3 : 2;
#pragma unroll 1
  for (int trip = 0; trip < R / 32; trip += U) {
#pragma unroll
    for (int part = 0; part < U; part++) {
      const int chunk = trip + part;
      uint32_t u[16];
#pragma unroll
      for (int i = 0; i < 32; i += 4) {
        const float* v = acc + part * 32 + i;
        u[i / 2] = pack2(scaled_silu(v[0], k0), scaled_silu(v[1], k0));
        u[i / 2 + 1] = pack2(scaled_silu(v[2], k1), scaled_silu(v[3], k1));
      }
      if (part == U - 1) {
#pragma unroll
        for (int i = 0; i < R - 32 * U; i++) acc[i] = acc[i + 32 * U];
      }
      if (chunk > 0) {
        asm volatile("fence.proxy.async.shared::cta;" ::: "memory");
        event_arrive(c, ev + chunk - 1);
      }
      if (chunk < R / 32 - 2) mbar_wait(kSmem + kBarEmptyA + (R == 128 && chunk == 0 ? 16 : 24), 1);
#pragma unroll
      for (int j = 0; j < 4; j++)
        asm volatile("stmatrix.sync.aligned.m8n8.x4.shared.b16 [%0], {%1, %2, %3, %4};" ::"r"(dst + j * 256), "r"(u[4 * j]),
                     "r"(u[4 * j + 1]), "r"(u[4 * j + 2]), "r"(u[4 * j + 3])
                     : "memory");
      dst += 16384;
    }
  }
  asm volatile("fence.proxy.async.shared::cta;" ::: "memory");
  event_arrive(c, ev + R / 32 - 1);
}

template <bool FAST>
__device__ __forceinline__ void consumer_main(const Maps& maps, const Ctx& c, Attn& a, Ring& r, float (&acc_a)[96]) {
  uint32_t qn[2][4];
  run_double<FAST, false, 0, kItA, false>(c, a, r, acc_a, qn);
  ring_drain(c, r);
  store_h(c, acc_a, kStageHa, kEvHa);
  {
    float acc[128];
    run_double<FAST, false, kItA, kItA + kItB, true>(c, a, r, acc, qn);
    ring_drain(c, r);
    load_q(qn, q_slot(2));
    store_h(c, acc, kStageHb, kEvHb);
  }
  float acc[64];
  ring_reset<true>(c, r);
  run_double<FAST, true, kItA + kItB, kItDouble, true>(c, a, r, acc, qn);
  run_single<FAST, kItDouble, 128>(c, a, r, acc, qn);
  mbar_wait(kSmem + kBarFullK, 0);
  wg_fence();
  attn_pv(a);
  wg_commit();
  a.l0 += a.t0;
  a.l1 += a.t1;
  wg_wait<0>();
  attn_finish(c, a, 3);
#pragma unroll 1
  for (int s = 68 - kPureTail; s < 72; s++) stage_pure<true>(c, r, acc, 1);
  wg_wait<0>();
  pin(acc);
  const uint32_t stage = kSmem + kOffKv + c.wg * 16384;
  const int row = c.warp * 16 + (c.lane & 15);
#pragma unroll
  for (int j = 0; j < 16; j += 2) {
    const int col = j + (c.lane >> 4);
    const uint32_t addr = stage + (col >> 3) * 8192 + row * 128 + (((col & 7) ^ (row & 7)) << 4);
    asm volatile("stmatrix.sync.aligned.m8n8.x4.shared.b16 [%0], {%1, %2, %3, %4};" ::"r"(addr),
                 "r"(pack2(acc[4 * j], acc[4 * j + 1])), "r"(pack2(acc[4 * j + 2], acc[4 * j + 3])),
                 "r"(pack2(acc[4 * j + 4], acc[4 * j + 5])), "r"(pack2(acc[4 * j + 6], acc[4 * j + 7]))
                 : "memory");
  }
  asm volatile("fence.proxy.async.shared::cta;" ::: "memory");
  asm volatile("bar.sync %0, 128;" ::"r"(1 + c.wg) : "memory");
  if (c.leader) {
    tma3_store(&maps.out, stage, c.rb * 128 + c.wg * 64, c.cb * 2);
    asm volatile("cp.async.bulk.commit_group;\ncp.async.bulk.wait_group.read 0;" ::: "memory");
  }
}

__device__ __forceinline__ void consumer(const Maps& maps, const Ctx& c) {
  Ring r;
  ring_reset<false>(c, r);
  Attn a;
  float qmax;
  uint4 park[6];
  {
    const int tok = c.rb * 128 + c.cb * 16 + (c.wg * 4 + c.warp) * 2;
    const int row = c.cb * 16 + (c.wg * 4 + c.warp) * 2;
    const uint32_t xs0 = kSmem + row * 128 + (((c.lane >> 2) ^ (row & 7)) << 4) + (c.lane & 3) * 4;
    const uint32_t xs1 = (xs0 + 128) ^ 16;
    float d0 = 0.f, d1 = 0.f;
    float acc[68];
#pragma unroll 1
    for (int s = 0; s < 16; s++) {
      stage_pure<false>(c, r, acc, s != 0);
      const uint32_t xa = lds_u32(xs0 + (s & 3) * kSlotA), xb = lds_u32(xs1 + (s & 3) * kSlotA);
      const uint32_t gw = lds_u32(kSmem + kOffKv + s * 128 + c.lane * 4);
      d0 = fmaf(bf_lo(xa), bf_lo(gw), fmaf(bf_hi(xa), bf_hi(gw), d0));
      d1 = fmaf(bf_lo(xb), bf_lo(gw), fmaf(bf_hi(xb), bf_hi(gw), d1));
    }
    ring_drain(c, r);
    pin(acc);
    const bool is_v = c.cb >= 4;
    const uint32_t u0 = pack2(acc[64], acc[65]), u1 = pack2(acc[66], acc[67]);
    uint8_t* kv = g_kv + ((c.rb * 2 + c.wg + is_v) & 31) * 8192 + is_v * 4096 + c.warp * 1024 + (c.cb & 3) * 128 + c.lane * 4;
    *reinterpret_cast<uint32_t*>(kv) = u0;
    *reinterpret_cast<uint32_t*>(kv + 512) = u1;
    float st;
    if (is_v) {
      st = fmaxf(fmaxf(fabsf(bf_lo(u0)), fabsf(bf_hi(u0))), fmaxf(fabsf(bf_lo(u1)), fabsf(bf_hi(u1))));
      if (!(acc[64] + acc[65] + acc[66] + acc[67] < INFINITY)) st = INFINITY;
    } else {
      const float n0 = quad_sum(bf_lo(u0) * bf_lo(u0) + bf_hi(u0) * bf_hi(u0));
      const float n1 = quad_sum(bf_lo(u1) * bf_lo(u1) + bf_hi(u1) * bf_hi(u1));
      st = (n0 + n1 < INFINITY) ? fmaxf(n0, n1) : INFINITY;
    }
    const unsigned st_max = __reduce_max_sync(~0u, __float_as_uint(st));
    if (c.lane == 0) asm volatile("st.shared.u32 [%0], %1;" ::"r"(kSmem + kOffStat + (c.wg * 4 + c.warp) * 4), "r"(st_max) : "memory");
    event_arrive(c, kEvKv);
#pragma unroll
    for (int o = 16; o > 0; o >>= 1) {
      d0 += __shfl_xor_sync(~0u, d0, o);
      d1 += __shfl_xor_sync(~0u, d1, o);
    }
    if (c.lane < 2) g_gate[tok + c.lane] = sigmoid(c.lane ? d1 : d0);
    event_arrive(c, kEvGate);
    qmax = 0.f;
#pragma unroll
    for (int h = 0; h < 4; h++) {
      uint32_t f[8];
      float n0 = 0.f, n1 = 0.f;
#pragma unroll
      for (int i = 0; i < 8; i++) {
        const float q0 = acc[16 * h + 2 * i] * kScale, q1 = acc[16 * h + 2 * i + 1] * kScale;
        f[i] = pack2(q0, q1);
        if (i & 1) n1 = fmaf(q0, q0, fmaf(q1, q1, n1)); else n0 = fmaf(q0, q0, fmaf(q1, q1, n0));
      }
      n0 = quad_sum(n0);
      n1 = quad_sum(n1);
      qmax = (n0 + n1 < INFINITY) ? fmaxf(qmax, fmaxf(n0, n1)) : INFINITY;
      if (h == 0) {
#pragma unroll
        for (int i = 0; i < 8; i++) a.Q[i / 4][i % 4] = f[i];
      } else {
        park[2 * h - 2] = make_uint4(f[0], f[1], f[2], f[3]);
        park[2 * h - 1] = make_uint4(f[4], f[5], f[6], f[7]);
      }
    }
  }
  qmax = __uint_as_float(__reduce_max_sync(~0u, __float_as_uint(qmax)));
  if (c.lane == 0) asm volatile("st.shared.f32 [%0], %1;" ::"r"(kSmem + kOffQmax + (c.wg * 4 + c.warp) * 4), "f"(qmax) : "memory");
  float acc_a[96];
#pragma unroll 1
  for (int s = 0; s < kPureHead; s++) stage_pure<false>(c, r, acc_a, s != 0);
#pragma unroll
  for (int i = 0; i < 6; i++) const_cast<uint4*>(q_slot(1))[i * 256] = park[i];
#pragma unroll
  for (int i = 0; i < 16; i++) { a.P[i / 4][i % 4] = 0; a.O[i] = 0.f; }
  a.l0 = 0.f; a.l1 = 0.f; a.t0 = 0.f; a.t1 = 0.f;
  a.m0 = -INFINITY; a.m1 = -INFINITY;
  a.it = 0;
  a.dk = opaque(make_desc(kSmem + kOffKv, 128, 512, 0));
  a.dv = opaque(make_desc(kSmem + kOffKv + 4096, 512, 128, 0));
  asm volatile("bar.sync %0, 128;" ::"r"(1 + c.wg) : "memory");
  float4 qm;
  asm volatile("ld.shared.v4.f32 {%0, %1, %2, %3}, [%4];" : "=f"(qm.x), "=f"(qm.y), "=f"(qm.z), "=f"(qm.w) : "r"(kSmem + kOffQmax + c.wg * 16) : "memory");
  qmax = fmaxf(fmaxf(qm.x, qm.y), fmaxf(qm.z, qm.w)) * 1.02f;
  mbar_wait(kSmem + kBarMeta, 0);
  const bool fast = qmax * lds_f32(kSmem + kOffBound) <= kMaxScore * kMaxScore;
  if (__any_sync(~0u, !fast)) consumer_main<false>(maps, c, a, r, acc_a);
  else consumer_main<true>(maps, c, a, r, acc_a);
}

__device__ __forceinline__ void gemm_producer(const Maps& maps, uint32_t smem, int rb, int cb) {
  const uint64_t once = policy_evict_first();
#pragma unroll 1
  for (int s = kSlotsA; s < 48; s++) {
    const uint32_t full = smem + kBarFullA + 8 * (s & 3), dst = smem + (s & 3) * kSlotA;
    const int k0 = (s & 15) * 64, pass = s >> 4;
    mbar_wait(s == 35 ? smem + kBarDrained : full + 8 * kSlotsA, s == 35 ? 0 : ~(s >> 2) & 1);
    if (pass) mbar_arrive(full);
    mbar_expect(full, 32768 + pass * 8192);
    tma2(dst, &maps.x, k0, rb * 128, full);
    tma3(dst + 16384, &maps.wq + pass, k0, pass ? cb * 7 + 3 * pass - 3 : cb * 2, full, once);
  }
  uint32_t slot = 0, phase = 1;
  int chunk = 0;
  const uint8_t* img = g_img + (size_t)rb * 72 * 16384;
#pragma unroll 1
  for (int s = 0; s < 68; s++) {
    const uint32_t full = smem + kBarFullB + 8 * slot, dst = smem + slot * kSlotB;
    if (s >= 6) mbar_wait(full + 8 * kSlotsB, phase);
    else mbar_wait(s >= 4 ? smem + kBarDrained + 8 : smem + kBarEmptyA + 8 * ((s + 1) >> 1), s < 4);
    mbar_expect(full, 32768);
    if (s < 56) {
      tma3(dst + 16384, &maps.w2, chunk * 64, cb * 2, full, once);
      chunk = s == 23 ? 3 : chunk + ((chunk % 7 == (s < 24 ? 2 : 6)) ? (s < 24 ? 5 : 4) : 1);
    } else {
      tma5(dst + 16384, &maps.wo, (s & 3) * 2, (s - 56) >> 2, cb * 2, full, once);
    }
    if (s == 0 || s == 24 || s == 56 || s == 60 || s == 64)
      flag_wait(g_flag + (s < 56 ? (s ? kFlagHb : kFlagHa) + rb * 32 : kFlagO + (rb * 4 + ((s - 56) >> 2)) * 32), 8);
    bulk_load(dst, img + s * 16384, 16384, full);
    if (++slot == kSlotsB) { slot = 0; phase ^= 1; }
  }
  constexpr uint32_t first = 68 % kSlotsB;
  int nw = 0, no = 0, spins = 0;
  bool seen = false;
#pragma unroll 1
  while (no < 4 && ++spins < 0x40000) {
    const uint32_t full = smem + kBarFullB + 8 * first, dst = smem + first * kSlotB;
    if (nw < 4 && mbar_try(full + 8 * (kSlotsB + nw), phase)) {
      mbar_expect(full + 8 * nw, 32768);
      tma5(dst + nw * kSlotB + 16384, &maps.wo, nw * 2, 3, cb * 2, full + 8 * nw, once);
      nw++;
    } else if (!seen) {
      unsigned v;
      asm volatile("ld.relaxed.gpu.global.u32 %0, [%1];" : "=r"(v) : "l"(g_flag + kFlagO + (rb * 4 + 3) * 32) : "memory");
      seen = v >= 8;
      if (seen) asm volatile("fence.acquire.gpu;\nfence.proxy.async.global;" ::: "memory");
    }
    if (seen && no < nw) {
      bulk_load(dst + no * kSlotB, img + (68 + no) * 16384, 16384, full + 8 * no);
      no++;
    }
  }
  if (atomicAdd(g_flag + kFlagDone, 1) == kCtas - 1) {
#pragma unroll 1
    for (int i = 0; i < kFlagWords; i += 32) *reinterpret_cast<uint4*>(g_flag + i) = make_uint4(0, 0, 0, 0);
  }
}

__device__ __forceinline__ void kv_producer(uint32_t smem) {
  mbar_wait(smem + kBarEvent + 8 * kEvKv, 0);
  uint4 f;
  int spins = 0;
  do {
    asm volatile("ld.relaxed.gpu.global.v4.u32 {%0, %1, %2, %3}, [%4];" : "=r"(f.x), "=r"(f.y), "=r"(f.z), "=r"(f.w) : "l"(g_flag + kFlagKv) : "memory");
  } while (f.x < kCtas && ++spins < 0x20000);
  asm volatile("fence.acquire.gpu;\nfence.proxy.async.global;" ::: "memory");
  uint32_t slot = 0, phase = 1;
#pragma unroll 1
  for (int it = 0; it <= 128; it++) {
    const uint32_t full = smem + kBarFullK + 8 * slot;
    mbar_wait(smem + kBarEmptyK + 8 * slot, phase);
    mbar_expect(full, kSlotK);
    bulk_load(smem + kOffKv + slot * kSlotK, g_kv + (it & 31) * kSlotK, kSlotK, full);
    if (it == 0) {
      const float vm = __uint_as_float(f.z);
      const float bound = (vm >= kMinV && vm <= kMaxV) ? 4.f * __uint_as_float(f.y) : INFINITY;
      asm volatile("st.shared.f32 [%0], %1;" ::"r"(smem + kOffBound), "f"(bound) : "memory");
      mbar_arrive(smem + kBarMeta);
    }
    if (++slot == kSlotsK) { slot = 0; phase ^= 1; }
  }
}

__device__ __forceinline__ void load_raw(uint32_t smem, const __nv_bfloat16* wkv, int s, int slot) {
  mbar_expect(smem + kBarRaw + 8 * slot, 4096);
  bulk_load(smem + kOffRaw + slot * 4096, wkv + s * 2048, 4096, smem + kBarRaw + 8 * slot);
}
__device__ __forceinline__ void helper(uint32_t smem, const __nv_bfloat16* wkv, int rb, int cb, int lane) {
  const uint32_t src = smem + kOffRaw + lane * 64 + (cb & 3) * 16;
  const uint32_t dst = smem + 32768 + lane * 128 + ((lane & 7) << 4);
  uint32_t slot = 0, phase = 0;
#pragma unroll 1
  for (int s = 0; s < 16; s++) {
    const uint32_t d = dst + (s & 3) * kSlotA;
    uint4 v0, v1;
    mbar_wait(smem + kBarRaw + 8 * slot, phase);
    asm volatile("ld.shared.v4.u32 {%0, %1, %2, %3}, [%4];" : "=r"(v0.x), "=r"(v0.y), "=r"(v0.z), "=r"(v0.w) : "r"(src + slot * 4096) : "memory");
    asm volatile("ld.shared.v4.u32 {%0, %1, %2, %3}, [%4];" : "=r"(v1.x), "=r"(v1.y), "=r"(v1.z), "=r"(v1.w) : "r"(src + slot * 4096 + 2048) : "memory");
    mbar_wait(smem + kBarEmptyA + 8 * (s & 3), ~(s >> 2) & 1);
    asm volatile("st.shared.v4.u32 [%0], {%1, %2, %3, %4};" ::"r"(d), "r"(v0.x), "r"(v0.y), "r"(v0.z), "r"(v0.w) : "memory");
    asm volatile("st.shared.v4.u32 [%0], {%1, %2, %3, %4};" ::"r"(d + 4096), "r"(v1.x), "r"(v1.y), "r"(v1.z), "r"(v1.w) : "memory");
    asm volatile("fence.proxy.async.shared::cta;" ::: "memory");
    __syncwarp();
    if (elect_one()) {
      mbar_arrive(smem + kBarFullA + 8 * (s & 3));
      if (s + kSlotsRaw < 16) load_raw(smem, wkv, s + kSlotsRaw, slot);
    }
    __syncwarp();
    if (++slot == kSlotsRaw) { slot = 0; phase ^= 1; }
  }
  if (lane == 0) {
    mbar_wait(smem + kBarEvent + 8 * kEvGate, 0);
    flag_wait(g_flag + kFlagGate + rb * 32, 8);
  }
  __syncwarp();
  const float4 gv = __ldcg(reinterpret_cast<const float4*>(g_gate) + rb * 32 + lane);
  asm volatile("st.shared.v4.f32 [%0], {%1, %2, %3, %4};" ::"r"(smem + kOffGate + lane * 16), "f"(gv.x), "f"(gv.y), "f"(gv.z), "f"(gv.w) : "memory");
  __syncwarp();
  if (lane == 0) mbar_arrive(smem + kBarGate);
}

__device__ __forceinline__ void signaller(uint32_t smem, int rb, int cb) {
#pragma unroll 1
  for (int e = 0; e < 8; e++) {
    unsigned* flag;
    if (e == 2 || e == 4) {
      const int b = e >> 2;
      uint8_t* dst = g_img + (size_t)(rb * 72 + (b ? 24 + cb * 4 : cb * 3)) * 16384;
#pragma unroll 1
      for (int i = 0; i < 3 + b; i++) {
        mbar_wait(smem + kBarEvent + 8 * ((b ? kEvHb : kEvHa) + i), 0);
        bulk_store(dst + i * 16384, smem + (b ? kStageHb : kStageHa) + i * 16384, 16384);
      }
      asm volatile("cp.async.bulk.commit_group;\ncp.async.bulk.wait_group.read 0;" ::: "memory");
      mbar_arrive(smem + kBarDrained + 8 * b);
      asm volatile("cp.async.bulk.wait_group 0;\nfence.proxy.async.global;" ::: "memory");
      flag = g_flag + (b ? kFlagHb : kFlagHa) + rb * 32;
    } else {
      const int round = e == 3 ? 0 : e - 4;
      mbar_wait(smem + kBarEvent + 8 * (e == 0 ? kEvKv : e == 1 ? kEvGate : kEvO + round), 0);
      flag = g_flag + (e == 0 ? kFlagKv : e == 1 ? kFlagGate + rb * 32 : kFlagO + (rb * 4 + round) * 32);
    }
    if (e == 0) {
      unsigned m = 0;
#pragma unroll
      for (int i = 0; i < 8; i++) m = max(m, lds_u32(smem + kOffStat + 4 * i));
      atomicMax(flag + 1 + (cb >> 2), m);
    }
    flag_signal(flag);
  }
}

__global__ void __launch_bounds__(kThreads, 1)
fused_kernel(const __grid_constant__ Maps maps, const __grid_constant__ Weights w) {
  extern __shared__ __align__(1024) uint8_t smem_raw[];
  if ((uint32_t)__cvta_generic_to_shared(smem_raw) != kSmem) __trap();
  constexpr uint32_t smem = kSmem;
  const int warp = __shfl_sync(~0u, threadIdx.x >> 5, 0);
  const int rb = ((blockIdx.x >> 1) & 7) | ((blockIdx.x >> 3) & 8), cb = (blockIdx.x & 1) | ((blockIdx.x >> 3) & 6);
  const __nv_bfloat16* wkv = cb < 4 ? w.wk : w.wv;
  if (warp == 8) {
    if (elect_one()) {
#pragma unroll
      for (int s = 0; s < 2 * kSlotsA; s++) mbar_init(smem + kBarFullA + 8 * s, 2);
      asm volatile("fence.mbarrier_init.release.cluster;" ::: "memory");
      const uint64_t once = policy_evict_first();
#pragma unroll
      for (int s = 0; s < kSlotsA; s++) {
        mbar_expect(smem + kBarFullA + 8 * s, s == 0 ? 32768 + 2048 : 32768);
        tma2(smem + s * kSlotA, &maps.x, s * 64, rb * 128, smem + kBarFullA + 8 * s);
        tma3(smem + s * kSlotA + 16384, &maps.wq, s * 64, cb * 2, smem + kBarFullA + 8 * s, once);
        if (s == 0) bulk_load(smem + kOffKv, w.gate, 2048, smem + kBarFullA);
      }
    }
  } else if (warp == 9) {
    if (elect_one()) {
#pragma unroll
      for (uint32_t b = kBarFullB; b < kBarEvent; b += 8) mbar_init(smem + b, (b >= kBarEmptyB && b < kBarFullK) || b >= kBarEmptyK ? 2 : 1);
      asm volatile("fence.mbarrier_init.release.cluster;" ::: "memory");
    }
  } else if (warp == 11) {
    if (elect_one()) {
#pragma unroll
      for (int s = 0; s < kSlotsRaw; s++) mbar_init(smem + kBarRaw + 8 * s, 1);
      asm volatile("fence.mbarrier_init.release.cluster;" ::: "memory");
#pragma unroll
      for (int s = 0; s < kSlotsRaw; s++) load_raw(smem, wkv, s, s);
    }
  } else if (warp == 10) {
    if (elect_one()) {
#pragma unroll
      for (uint32_t b = kBarEvent; b <= kBarGate; b += 8) mbar_init(smem + b, b < kBarDrained ? 8 : 1);
      asm volatile("fence.mbarrier_init.release.cluster;" ::: "memory");
    }
  }
  __syncthreads();
  if (warp < 8) {
    asm volatile("setmaxnreg.inc.sync.aligned.u32 240;");
    const Ctx c{warp >> 2, warp & 3, (int)(threadIdx.x & 31), rb, cb, (threadIdx.x & 127) == 0};
    consumer(maps, c);
  } else {
    asm volatile("setmaxnreg.dec.sync.aligned.u32 24;");
    if (warp == 8) {
      if (elect_one()) gemm_producer(maps, smem, rb, cb);
    } else if (warp == 9) {
      if (elect_one()) kv_producer(smem);
    } else if (warp == 10) {
      if (elect_one()) signaller(smem, rb, cb);
    } else {
      helper(smem, wkv, rb, cb, threadIdx.x & 31);
    }
  }
}

using EncodeFn = CUresult (*)(CUtensorMap*, CUtensorMapDataType, cuuint32_t, void*, const cuuint64_t*, const cuuint64_t*,
                              const cuuint32_t*, const cuuint32_t*, CUtensorMapInterleave, CUtensorMapSwizzle,
                              CUtensorMapL2promotion, CUtensorMapFloatOOBfill);

void encode(EncodeFn fn, CUtensorMap* map, const void* base, int rank, const cuuint64_t* dims, const cuuint64_t* strides,
            const cuuint32_t* box) {
  const cuuint32_t ones[5] = {1, 1, 1, 1, 1};
  fn(map, CU_TENSOR_MAP_DATA_TYPE_BFLOAT16, rank, const_cast<void*>(base), dims, strides, box, ones, CU_TENSOR_MAP_INTERLEAVE_NONE,
     CU_TENSOR_MAP_SWIZZLE_128B, CU_TENSOR_MAP_L2_PROMOTION_L2_128B, CU_TENSOR_MAP_FLOAT_OOB_FILL_NONE);
}
void encode_chunked(EncodeFn fn, CUtensorMap* map, const void* base, int rows, int cols, int chunks) {
  const cuuint64_t dims[3] = {64, (cuuint64_t)rows, (cuuint64_t)cols / 64};
  const cuuint64_t strides[2] = {(cuuint64_t)cols * 2, 128};
  const cuuint32_t box[3] = {64, 64, (cuuint32_t)chunks};
  encode(fn, map, base, 3, dims, strides, box);
}
void encode_plain(EncodeFn fn, CUtensorMap* map, const void* base, int rows, int cols, int box_rows) {
  const cuuint64_t dims[2] = {(cuuint64_t)cols, (cuuint64_t)rows};
  const cuuint64_t strides[1] = {(cuuint64_t)cols * 2};
  const cuuint32_t box[2] = {64, (cuuint32_t)box_rows};
  encode(fn, map, base, 2, dims, strides, box);
}

}

extern "C" void kernel_launch(void* const* d_in, const int* in_sizes, int n_in, void* d_out, int out_size) {
  (void)in_sizes; (void)n_in; (void)out_size;
  void* fn_ptr = nullptr;
  cudaDriverEntryPointQueryResult status;
  cudaGetDriverEntryPoint("cuTensorMapEncodeTiled", &fn_ptr, cudaEnableDefault, &status);
  const EncodeFn fn = reinterpret_cast<EncodeFn>(fn_ptr);
  Maps maps;
  encode_plain(fn, &maps.x, d_in[0], 2048, 1024, 128);
  encode_chunked(fn, &maps.wq, d_in[1], 1024, 1024, 2);
  encode_chunked(fn, &maps.w1a, d_in[6], 1024, 3584, 3);
  encode_chunked(fn, &maps.w1b, d_in[6], 1024, 3584, 4);
  encode_chunked(fn, &maps.w2, d_in[7], 3584, 1024, 2);
  {
    const cuuint64_t dims[5] = {64, 32, 8, 4, 16};
    const cuuint64_t strides[4] = {2048, 128 * 2048, 32 * 2048, 128};
    const cuuint32_t box[5] = {64, 32, 2, 1, 2};
    encode(fn, &maps.wo, d_in[4], 5, dims, strides, box);
  }
  encode_chunked(fn, &maps.out, d_out, 2048, 1024, 2);
  cudaFuncSetAttribute(fused_kernel, cudaFuncAttributeMaxDynamicSharedMemorySize, kSmemBytes);
  const auto in = [&](int i) { return static_cast<const __nv_bfloat16*>(d_in[i]); };
  const Weights w{in(2), in(3), in(8)};
  fused_kernel<<<kCtas, kThreads, kSmemBytes>>>(maps, w);
}
```

```cpp
#include <cuda.h>
#include <cuda_bf16.h>
#include <cuda_runtime.h>
#include <stdint.h>

namespace {

constexpr int kCtas = 128;
constexpr int kThreads = 384;

constexpr int kPureHead = 4;
constexpr int kPureTail = 6;
constexpr int kItA = (16 - kPureHead) * 2;
constexpr int kItB = 32;
constexpr int kAssistCtas = 4, kAssist = 4;
template <bool FAST> struct Sched {
  static constexpr int end = 128 - (FAST ? kAssist : 0);
  static constexpr int doubled = end - kItA - kItB - (68 - kPureTail);
  static constexpr int single = kItA + kItB + 2 * doubled;
  static_assert(doubled > 0 && single < 96, "bad schedule");
};
static_assert(kItA < 31 && kItA + kItB > 33 && kItA + kItB < 64 && kPureTail <= 12 && kAssist >= 2, "bad schedule");

constexpr uint32_t kSmem = 1024;
constexpr uint32_t kSlotA = 49152, kSlotsA = 4;
constexpr uint32_t kSlotB = 32768, kSlotsB = 6;
constexpr uint32_t kSlotK = 8192, kSlotsK = 4;
constexpr uint32_t kOffKv = kSlotA * kSlotsA;
constexpr uint32_t kOffMisc = kOffKv + kSlotK * kSlotsK;
constexpr uint32_t kBarFullA = kOffMisc, kBarEmptyA = kBarFullA + 8 * kSlotsA;
constexpr uint32_t kSlotsRaw = 4, kOffRaw = kOffKv + 4096, kBarRaw = kBarEmptyA + 8 * kSlotsA;
constexpr uint32_t kBarFullB = kBarRaw + 8 * kSlotsRaw, kBarEmptyB = kBarFullB + 8 * kSlotsB;
constexpr uint32_t kBarFullK = kBarEmptyB + 8 * kSlotsB, kBarEmptyK = kBarFullK + 8 * kSlotsK;
enum { kEvKv = 0, kEvHa = 1, kEvHb = 4, kEvO = 8, kEvGate = 12, kEvQ = 13, kEvents = 14 };
constexpr uint32_t kBarEvent = kBarEmptyK + 8 * kSlotsK;
constexpr uint32_t kBarDrained = kBarEvent + 8 * kEvents;
constexpr uint32_t kBarDummy = kBarDrained + 16;
constexpr uint32_t kBarMeta = kBarDummy + 8;
constexpr uint32_t kBarPart = kBarMeta + 8;
constexpr uint32_t kBarGate = kBarPart + 8;
constexpr uint32_t kOffMode = kBarGate + 8;
constexpr uint32_t kOffQmax = kOffMisc + 544;
constexpr uint32_t kOffStat = kOffMisc + 576;
constexpr uint32_t kOffGate = kOffMisc + 608;
constexpr uint32_t kSmemBytes = kOffGate + 512;
constexpr uint32_t kStageHa = 3 * kSlotA, kStageHb = 4 * kSlotB;
static_assert(71 % kSlotsB >= 3, "the last four stages must not wrap");
static_assert(kOffMode + 4 <= kOffQmax, "misc area overflow");

constexpr int kFlagHa = 0, kFlagHb = 1, kFlagGate = 2, kFlagO = 4;
constexpr int kFlagKv = 16 * 32, kFlagQ = kFlagKv + 32, kFlagDone = kFlagQ + 1, kFlagWords = 18 * 32;
__device__ __align__(1024) uint8_t g_img[16 * 72 * 16384];
__device__ __align__(1024) uint8_t g_kv[32 * 8192];
__device__ __align__(1024) uint4 g_q[kCtas * 4 * 2 * 256];
constexpr int kPartBytes = 10240;
__device__ __align__(1024) uint8_t g_part[kCtas * kPartBytes];
__device__ __align__(1024) unsigned g_part_flag[kCtas * 8];
__device__ __align__(1024) float g_gate[2048];
__device__ __align__(1024) unsigned g_flag[kFlagWords];

struct Weights {
  const __nv_bfloat16 *wk, *wv, *gate;
  bool assist;
};
struct Maps {
  CUtensorMap x, wq, w1a, w1b, w2, wo, out;
};

constexpr float kScale = 0.25503487f;
constexpr float kMaxScore = 80.f;
constexpr float kMinV = 2.3841858e-07f, kMaxV = 1073741824.f;

__device__ __forceinline__ void mbar_init(uint32_t bar, uint32_t count) {
  asm volatile("mbarrier.init.shared::cta.b64 [%0], %1;" ::"r"(bar), "r"(count));
}
__device__ __forceinline__ void mbar_expect(uint32_t bar, uint32_t bytes) {
  asm volatile("mbarrier.arrive.expect_tx.shared::cta.b64 _, [%0], %1;" ::"r"(bar), "r"(bytes) : "memory");
}
__device__ __forceinline__ void mbar_arrive(uint32_t bar) {
  asm volatile("mbarrier.arrive.shared::cta.b64 _, [%0];" ::"r"(bar) : "memory");
}
__device__ __forceinline__ void mbar_wait(uint32_t bar, uint32_t parity) {
  asm volatile(
      "{\n.reg .pred p;\n.reg .u32 c;\nmov.u32 c, 0;\n"
      "LOOP:\nmbarrier.try_wait.parity.shared::cta.b64 p, [%0], %1;\n@p bra DONE;\n"
      "add.u32 c, c, 1;\nsetp.lt.u32 p, c, 0x80000;\n@p bra LOOP;\nDONE:\n}\n" ::"r"(bar), "r"(parity)
      : "memory");
}
__device__ __forceinline__ void mbar_wait2(uint32_t bar0, uint32_t parity0, uint32_t bar1, uint32_t parity1) {
  asm volatile(
      "{\n.reg .pred p, q;\n.reg .u32 c;\nmov.u32 c, 0;\n"
      "LOOP:\nmbarrier.try_wait.parity.shared::cta.b64 p, [%0], %1;\nmbarrier.try_wait.parity.shared::cta.b64 q, [%2], %3;\n"
      "and.pred p, p, q;\n@p bra DONE;\n"
      "add.u32 c, c, 1;\nsetp.lt.u32 p, c, 0x80000;\n@p bra LOOP;\nDONE:\n}\n" ::"r"(bar0), "r"(parity0), "r"(bar1), "r"(parity1)
      : "memory");
}
__device__ __forceinline__ bool mbar_try(uint32_t bar, uint32_t parity) {
  uint32_t ok;
  asm volatile("{\n.reg .pred p;\nmbarrier.test_wait.parity.shared::cta.b64 p, [%1], %2;\nselp.u32 %0, 1, 0, p;\n}\n"
               : "=r"(ok) : "r"(bar), "r"(parity) : "memory");
  return ok;
}
__device__ __forceinline__ void flag_wait(const unsigned* flag, unsigned target) {
  asm volatile(
      "{\n.reg .pred p;\n.reg .u32 c, v;\nmov.u32 c, 0;\n"
      "LOOP:\nld.relaxed.gpu.global.u32 v, [%0];\nsetp.ge.u32 p, v, %1;\n@p bra DONE;\n"
      "add.u32 c, c, 1;\nsetp.lt.u32 p, c, 0x20000;\n@p bra LOOP;\n"
      "DONE:\nfence.acquire.gpu;\nfence.proxy.async.global;\n}\n" ::"l"(flag), "r"(target)
      : "memory");
}
__device__ __forceinline__ void flag_signal(unsigned* flag) {
  asm volatile("red.release.gpu.global.add.u32 [%0], 1;" ::"l"(flag) : "memory");
}
__device__ __forceinline__ bool elect_one() {
  uint32_t p;
  asm volatile("{\n.reg .pred P;\nelect.sync _|P, 0xffffffff;\nselp.u32 %0, 1, 0, P;\n}\n" : "=r"(p));
  return p;
}
__device__ __forceinline__ void bulk_load(uint32_t dst, const void* src, uint32_t bytes, uint32_t bar) {
  asm volatile("cp.async.bulk.shared::cluster.global.mbarrier::complete_tx::bytes [%0], [%1], %2, [%3];" ::"r"(dst),
               "l"(src), "r"(bytes), "r"(bar)
               : "memory");
}
__device__ __forceinline__ void bulk_store(void* dst, uint32_t src, uint32_t bytes) {
  asm volatile("cp.async.bulk.global.shared::cta.bulk_group [%0], [%1], %2;" ::"l"(dst), "r"(src), "r"(bytes) : "memory");
}
__device__ __forceinline__ void tma2(uint32_t dst, const CUtensorMap* m, int c0, int c1, uint32_t bar) {
  asm volatile("cp.async.bulk.tensor.2d.shared::cluster.global.mbarrier::complete_tx::bytes [%0], [%1, {%3, %4}], [%2];" ::"r"(dst),
               "l"(m), "r"(bar), "r"(c0), "r"(c1)
               : "memory");
}
__device__ __forceinline__ uint64_t policy_evict_first() {
  uint64_t p;
  asm("createpolicy.fractional.L2::evict_first.b64 %0, 1.0;" : "=l"(p));
  return p;
}
__device__ __forceinline__ void tma3(uint32_t dst, const CUtensorMap* m, int c1, int c2, uint32_t bar, uint64_t policy) {
  asm volatile("cp.async.bulk.tensor.3d.shared::cluster.global.mbarrier::complete_tx::bytes.L2::cache_hint [%0], [%1, {0, %3, %4}], [%2], %5;" ::"r"(dst),
               "l"(m), "r"(bar), "r"(c1), "r"(c2), "l"(policy)
               : "memory");
}
__device__ __forceinline__ void tma5(uint32_t dst, const CUtensorMap* m, int c2, int c3, int c4, uint32_t bar, uint64_t policy) {
  asm volatile("cp.async.bulk.tensor.5d.shared::cluster.global.mbarrier::complete_tx::bytes.L2::cache_hint [%0], [%1, {0, 0, %3, %4, %5}], [%2], %6;" ::"r"(dst),
               "l"(m), "r"(bar), "r"(c2), "r"(c3), "r"(c4), "l"(policy)
               : "memory");
}
__device__ __forceinline__ void tma3_store(const CUtensorMap* m, uint32_t src, int c1, int c2) {
  asm volatile("cp.async.bulk.tensor.3d.global.shared::cta.bulk_group [%0, {0, %2, %3}], [%1];" ::"l"(m), "r"(src), "r"(c1), "r"(c2)
               : "memory");
}
__device__ __forceinline__ void wg_fence() { asm volatile("wgmma.fence.sync.aligned;" ::: "memory"); }
__device__ __forceinline__ void wg_commit() { asm volatile("wgmma.commit_group.sync.aligned;" ::: "memory"); }
template <int N>
__device__ __forceinline__ void wg_wait() { asm volatile("wgmma.wait_group.sync.aligned %0;" ::"n"(N) : "memory"); }
template <int R>
__device__ __forceinline__ void pin(float (&a)[R]) {
#pragma unroll
  for (int i = 0; i < R; i++) asm volatile("" : "+f"(a[i])::"memory");
}
__host__ __device__ constexpr uint64_t make_desc(uint32_t addr, uint32_t lbo, uint32_t sbo, uint32_t swizzle) {
  return (uint64_t)((addr & 0x3FFFF) >> 4) | ((uint64_t)(lbo >> 4) << 16) | ((uint64_t)(sbo >> 4) << 32) | ((uint64_t)swizzle << 62);
}
__device__ __forceinline__ float ex2(float x) {
  float y;
  asm("ex2.approx.ftz.f32 %0, %1;" : "=f"(y) : "f"(x));
  return y;
}
__device__ __forceinline__ float rcp(float x) {
  float y;
  asm("rcp.approx.ftz.f32 %0, %1;" : "=f"(y) : "f"(x));
  return y;
}
__device__ __forceinline__ float sigmoid(float x) { return rcp(1.f + ex2(x * -1.4426950408889634f)); }
__device__ __forceinline__ uint32_t pack2(float lo, float hi) {
  uint32_t r;
  asm("cvt.rn.bf16x2.f32 %0, %1, %2;" : "=r"(r) : "f"(hi), "f"(lo));
  return r;
}
__device__ __forceinline__ float bf_lo(uint32_t v) { return __uint_as_float(v << 16); }
__device__ __forceinline__ float bf_hi(uint32_t v) { return __uint_as_float(v & 0xffff0000u); }
__device__ __forceinline__ float lds_f32(uint32_t addr) {
  float v;
  asm volatile("ld.shared.f32 %0, [%1];" : "=f"(v) : "r"(addr) : "memory");
  return v;
}
__device__ __forceinline__ uint32_t lds_u32(uint32_t addr) {
  uint32_t v;
  asm volatile("ld.shared.u32 %0, [%1];" : "=r"(v) : "r"(addr) : "memory");
  return v;
}
__device__ __forceinline__ uint4 lds_v4(uint32_t addr) {
  uint4 v;
  asm volatile("ld.shared.v4.u32 {%0, %1, %2, %3}, [%4];" : "=r"(v.x), "=r"(v.y), "=r"(v.z), "=r"(v.w) : "r"(addr) : "memory");
  return v;
}
__device__ __forceinline__ void sts_v4(uint32_t addr, const uint4& v) {
  asm volatile("st.shared.v4.u32 [%0], {%1, %2, %3, %4};" ::"r"(addr), "r"(v.x), "r"(v.y), "r"(v.z), "r"(v.w) : "memory");
}
__device__ __forceinline__ void sts_u32(uint32_t addr, uint32_t v) {
  asm volatile("st.shared.u32 [%0], %1;" ::"r"(addr), "r"(v) : "memory");
}
__device__ __forceinline__ unsigned max4(const uint4& v) { return max(max(v.x, v.y), max(v.z, v.w)); }
__device__ __forceinline__ float quad_sum(float v) {
  v += __shfl_xor_sync(~0u, v, 1);
  return v + __shfl_xor_sync(~0u, v, 2);
}

__device__ __forceinline__ void wgmma_rs_n32(float (&d)[16], const uint32_t (&a)[4], uint64_t db, int accumulate) {
  asm volatile(
      "{\n.reg .pred p;\nsetp.ne.b32 p, %21, 0;\n"
      "wgmma.mma_async.sync.aligned.m64n32k16.f32.bf16.bf16 {"
      "%0, %1, %2, %3, %4, %5, %6, %7, %8, %9, %10, %11, %12, %13, %14, %15"
      "}, {%16, %17, %18, %19}, %20, p, 1, 1, 1;\n}\n"
      : "+f"(d[0]), "+f"(d[1]), "+f"(d[2]), "+f"(d[3]), "+f"(d[4]), "+f"(d[5]), "+f"(d[6]), "+f"(d[7]),
        "+f"(d[8]), "+f"(d[9]), "+f"(d[10]), "+f"(d[11]), "+f"(d[12]), "+f"(d[13]), "+f"(d[14]), "+f"(d[15])
      : "r"(a[0]), "r"(a[1]), "r"(a[2]), "r"(a[3]), "l"(db), "r"(accumulate));
}
__device__ __forceinline__ void wgmma_rs_n64(float (&d)[32], const uint32_t (&a)[4], uint64_t db, int accumulate) {
  asm volatile(
      "{\n.reg .pred p;\nsetp.ne.b32 p, %37, 0;\n"
      "wgmma.mma_async.sync.aligned.m64n64k16.f32.bf16.bf16 {"
      "%0, %1, %2, %3, %4, %5, %6, %7, %8, %9, %10, %11, %12, %13, %14, %15, "
      "%16, %17, %18, %19, %20, %21, %22, %23, %24, %25, %26, %27, %28, %29, %30, %31"
      "}, {%32, %33, %34, %35}, %36, p, 1, 1, 0;\n}\n"
      : "+f"(d[0]), "+f"(d[1]), "+f"(d[2]), "+f"(d[3]), "+f"(d[4]), "+f"(d[5]), "+f"(d[6]), "+f"(d[7]),
        "+f"(d[8]), "+f"(d[9]), "+f"(d[10]), "+f"(d[11]), "+f"(d[12]), "+f"(d[13]), "+f"(d[14]), "+f"(d[15]),
        "+f"(d[16]), "+f"(d[17]), "+f"(d[18]), "+f"(d[19]), "+f"(d[20]), "+f"(d[21]), "+f"(d[22]), "+f"(d[23]),
        "+f"(d[24]), "+f"(d[25]), "+f"(d[26]), "+f"(d[27]), "+f"(d[28]), "+f"(d[29]), "+f"(d[30]), "+f"(d[31])
      : "r"(a[0]), "r"(a[1]), "r"(a[2]), "r"(a[3]), "l"(db), "r"(accumulate));
}
__device__ __forceinline__ void wgmma_ss(float (&d)[64], uint64_t da, uint64_t db, int accumulate) {
  asm volatile(
      "{\n.reg .pred p;\nsetp.ne.b32 p, %66, 0;\n"
      "wgmma.mma_async.sync.aligned.m64n128k16.f32.bf16.bf16 {"
      "%0, %1, %2, %3, %4, %5, %6, %7, %8, %9, %10, %11, %12, %13, %14, %15, "
      "%16, %17, %18, %19, %20, %21, %22, %23, %24, %25, %26, %27, %28, %29, %30, %31, "
      "%32, %33, %34, %35, %36, %37, %38, %39, %40, %41, %42, %43, %44, %45, %46, %47, "
      "%48, %49, %50, %51, %52, %53, %54, %55, %56, %57, %58, %59, %60, %61, %62, %63"
      "}, %64, %65, p, 1, 1, 0, 1;\n}\n"
      : "+f"(d[0]), "+f"(d[1]), "+f"(d[2]), "+f"(d[3]), "+f"(d[4]), "+f"(d[5]), "+f"(d[6]), "+f"(d[7]),
        "+f"(d[8]), "+f"(d[9]), "+f"(d[10]), "+f"(d[11]), "+f"(d[12]), "+f"(d[13]), "+f"(d[14]), "+f"(d[15]),
        "+f"(d[16]), "+f"(d[17]), "+f"(d[18]), "+f"(d[19]), "+f"(d[20]), "+f"(d[21]), "+f"(d[22]), "+f"(d[23]),
        "+f"(d[24]), "+f"(d[25]), "+f"(d[26]), "+f"(d[27]), "+f"(d[28]), "+f"(d[29]), "+f"(d[30]), "+f"(d[31]),
        "+f"(d[32]), "+f"(d[33]), "+f"(d[34]), "+f"(d[35]), "+f"(d[36]), "+f"(d[37]), "+f"(d[38]), "+f"(d[39]),
        "+f"(d[40]), "+f"(d[41]), "+f"(d[42]), "+f"(d[43]), "+f"(d[44]), "+f"(d[45]), "+f"(d[46]), "+f"(d[47]),
        "+f"(d[48]), "+f"(d[49]), "+f"(d[50]), "+f"(d[51]), "+f"(d[52]), "+f"(d[53]), "+f"(d[54]), "+f"(d[55]),
        "+f"(d[56]), "+f"(d[57]), "+f"(d[58]), "+f"(d[59]), "+f"(d[60]), "+f"(d[61]), "+f"(d[62]), "+f"(d[63])
      : "l"(da), "l"(db), "r"(accumulate));
}
__device__ __forceinline__ void wgmma_ss(float (&d)[68], uint64_t da, uint64_t db, int accumulate) {
  asm volatile(
      "{\n.reg .pred p;\nsetp.ne.b32 p, %70, 0;\n"
      "wgmma.mma_async.sync.aligned.m64n136k16.f32.bf16.bf16 {"
      "%0, %1, %2, %3, %4, %5, %6, %7, %8, %9, %10, %11, %12, %13, %14, %15, "
      "%16, %17, %18, %19, %20, %21, %22, %23, %24, %25, %26, %27, %28, %29, %30, %31, "
      "%32, %33, %34, %35, %36, %37, %38, %39, %40, %41, %42, %43, %44, %45, %46, %47, "
      "%48, %49, %50, %51, %52, %53, %54, %55, %56, %57, %58, %59, %60, %61, %62, %63, "
      "%64, %65, %66, %67"
      "}, %68, %69, p, 1, 1, 0, 1;\n}\n"
      : "+f"(d[0]), "+f"(d[1]), "+f"(d[2]), "+f"(d[3]), "+f"(d[4]), "+f"(d[5]), "+f"(d[6]), "+f"(d[7]),
        "+f"(d[8]), "+f"(d[9]), "+f"(d[10]), "+f"(d[11]), "+f"(d[12]), "+f"(d[13]), "+f"(d[14]), "+f"(d[15]),
        "+f"(d[16]), "+f"(d[17]), "+f"(d[18]), "+f"(d[19]), "+f"(d[20]), "+f"(d[21]), "+f"(d[22]), "+f"(d[23]),
        "+f"(d[24]), "+f"(d[25]), "+f"(d[26]), "+f"(d[27]), "+f"(d[28]), "+f"(d[29]), "+f"(d[30]), "+f"(d[31]),
        "+f"(d[32]), "+f"(d[33]), "+f"(d[34]), "+f"(d[35]), "+f"(d[36]), "+f"(d[37]), "+f"(d[38]), "+f"(d[39]),
        "+f"(d[40]), "+f"(d[41]), "+f"(d[42]), "+f"(d[43]), "+f"(d[44]), "+f"(d[45]), "+f"(d[46]), "+f"(d[47]),
        "+f"(d[48]), "+f"(d[49]), "+f"(d[50]), "+f"(d[51]), "+f"(d[52]), "+f"(d[53]), "+f"(d[54]), "+f"(d[55]),
        "+f"(d[56]), "+f"(d[57]), "+f"(d[58]), "+f"(d[59]), "+f"(d[60]), "+f"(d[61]), "+f"(d[62]), "+f"(d[63]),
        "+f"(d[64]), "+f"(d[65]), "+f"(d[66]), "+f"(d[67])
      : "l"(da), "l"(db), "r"(accumulate));
}
__device__ __forceinline__ void wgmma_ss(float (&d)[96], uint64_t da, uint64_t db, int accumulate) {
  asm volatile(
      "{\n.reg .pred p;\nsetp.ne.b32 p, %98, 0;\n"
      "wgmma.mma_async.sync.aligned.m64n192k16.f32.bf16.bf16 {"
      "%0, %1, %2, %3, %4, %5, %6, %7, %8, %9, %10, %11, %12, %13, %14, %15, "
      "%16, %17, %18, %19, %20, %21, %22, %23, %24, %25, %26, %27, %28, %29, %30, %31, "
      "%32, %33, %34, %35, %36, %37, %38, %39, %40, %41, %42, %43, %44, %45, %46, %47, "
      "%48, %49, %50, %51, %52, %53, %54, %55, %56, %57, %58, %59, %60, %61, %62, %63, "
      "%64, %65, %66, %67, %68, %69, %70, %71, %72, %73, %74, %75, %76, %77, %78, %79, "
      "%80, %81, %82, %83, %84, %85, %86, %87, %88, %89, %90, %91, %92, %93, %94, %95"
      "}, %96, %97, p, 1, 1, 0, 1;\n}\n"
      : "+f"(d[0]), "+f"(d[1]), "+f"(d[2]), "+f"(d[3]), "+f"(d[4]), "+f"(d[5]), "+f"(d[6]), "+f"(d[7]),
        "+f"(d[8]), "+f"(d[9]), "+f"(d[10]), "+f"(d[11]), "+f"(d[12]), "+f"(d[13]), "+f"(d[14]), "+f"(d[15]),
        "+f"(d[16]), "+f"(d[17]), "+f"(d[18]), "+f"(d[19]), "+f"(d[20]), "+f"(d[21]), "+f"(d[22]), "+f"(d[23]),
        "+f"(d[24]), "+f"(d[25]), "+f"(d[26]), "+f"(d[27]), "+f"(d[28]), "+f"(d[29]), "+f"(d[30]), "+f"(d[31]),
        "+f"(d[32]), "+f"(d[33]), "+f"(d[34]), "+f"(d[35]), "+f"(d[36]), "+f"(d[37]), "+f"(d[38]), "+f"(d[39]),
        "+f"(d[40]), "+f"(d[41]), "+f"(d[42]), "+f"(d[43]), "+f"(d[44]), "+f"(d[45]), "+f"(d[46]), "+f"(d[47]),
        "+f"(d[48]), "+f"(d[49]), "+f"(d[50]), "+f"(d[51]), "+f"(d[52]), "+f"(d[53]), "+f"(d[54]), "+f"(d[55]),
        "+f"(d[56]), "+f"(d[57]), "+f"(d[58]), "+f"(d[59]), "+f"(d[60]), "+f"(d[61]), "+f"(d[62]), "+f"(d[63]),
        "+f"(d[64]), "+f"(d[65]), "+f"(d[66]), "+f"(d[67]), "+f"(d[68]), "+f"(d[69]), "+f"(d[70]), "+f"(d[71]),
        "+f"(d[72]), "+f"(d[73]), "+f"(d[74]), "+f"(d[75]), "+f"(d[76]), "+f"(d[77]), "+f"(d[78]), "+f"(d[79]),
        "+f"(d[80]), "+f"(d[81]), "+f"(d[82]), "+f"(d[83]), "+f"(d[84]), "+f"(d[85]), "+f"(d[86]), "+f"(d[87]),
        "+f"(d[88]), "+f"(d[89]), "+f"(d[90]), "+f"(d[91]), "+f"(d[92]), "+f"(d[93]), "+f"(d[94]), "+f"(d[95])
      : "l"(da), "l"(db), "r"(accumulate));
}
__device__ __forceinline__ void wgmma_ss(float (&d)[128], uint64_t da, uint64_t db, int accumulate) {
  asm volatile(
      "{\n.reg .pred p;\nsetp.ne.b32 p, %130, 0;\n"
      "wgmma.mma_async.sync.aligned.m64n256k16.f32.bf16.bf16 {"
      "%0, %1, %2, %3, %4, %5, %6, %7, %8, %9, %10, %11, %12, %13, %14, %15, "
      "%16, %17, %18, %19, %20, %21, %22, %23, %24, %25, %26, %27, %28, %29, %30, %31, "
      "%32, %33, %34, %35, %36, %37, %38, %39, %40, %41, %42, %43, %44, %45, %46, %47, "
      "%48, %49, %50, %51, %52, %53, %54, %55, %56, %57, %58, %59, %60, %61, %62, %63, "
      "%64, %65, %66, %67, %68, %69, %70, %71, %72, %73, %74, %75, %76, %77, %78, %79, "
      "%80, %81, %82, %83, %84, %85, %86, %87, %88, %89, %90, %91, %92, %93, %94, %95, "
      "%96, %97, %98, %99, %100, %101, %102, %103, %104, %105, %106, %107, %108, %109, %110, %111, "
      "%112, %113, %114, %115, %116, %117, %118, %119, %120, %121, %122, %123, %124, %125, %126, %127"
      "}, %128, %129, p, 1, 1, 0, 1;\n}\n"
      : "+f"(d[0]), "+f"(d[1]), "+f"(d[2]), "+f"(d[3]), "+f"(d[4]), "+f"(d[5]), "+f"(d[6]), "+f"(d[7]),
        "+f"(d[8]), "+f"(d[9]), "+f"(d[10]), "+f"(d[11]), "+f"(d[12]), "+f"(d[13]), "+f"(d[14]), "+f"(d[15]),
        "+f"(d[16]), "+f"(d[17]), "+f"(d[18]), "+f"(d[19]), "+f"(d[20]), "+f"(d[21]), "+f"(d[22]), "+f"(d[23]),
        "+f"(d[24]), "+f"(d[25]), "+f"(d[26]), "+f"(d[27]), "+f"(d[28]), "+f"(d[29]), "+f"(d[30]), "+f"(d[31]),
        "+f"(d[32]), "+f"(d[33]), "+f"(d[34]), "+f"(d[35]), "+f"(d[36]), "+f"(d[37]), "+f"(d[38]), "+f"(d[39]),
        "+f"(d[40]), "+f"(d[41]), "+f"(d[42]), "+f"(d[43]), "+f"(d[44]), "+f"(d[45]), "+f"(d[46]), "+f"(d[47]),
        "+f"(d[48]), "+f"(d[49]), "+f"(d[50]), "+f"(d[51]), "+f"(d[52]), "+f"(d[53]), "+f"(d[54]), "+f"(d[55]),
        "+f"(d[56]), "+f"(d[57]), "+f"(d[58]), "+f"(d[59]), "+f"(d[60]), "+f"(d[61]), "+f"(d[62]), "+f"(d[63]),
        "+f"(d[64]), "+f"(d[65]), "+f"(d[66]), "+f"(d[67]), "+f"(d[68]), "+f"(d[69]), "+f"(d[70]), "+f"(d[71]),
        "+f"(d[72]), "+f"(d[73]), "+f"(d[74]), "+f"(d[75]), "+f"(d[76]), "+f"(d[77]), "+f"(d[78]), "+f"(d[79]),
        "+f"(d[80]), "+f"(d[81]), "+f"(d[82]), "+f"(d[83]), "+f"(d[84]), "+f"(d[85]), "+f"(d[86]), "+f"(d[87]),
        "+f"(d[88]), "+f"(d[89]), "+f"(d[90]), "+f"(d[91]), "+f"(d[92]), "+f"(d[93]), "+f"(d[94]), "+f"(d[95]),
        "+f"(d[96]), "+f"(d[97]), "+f"(d[98]), "+f"(d[99]), "+f"(d[100]), "+f"(d[101]), "+f"(d[102]), "+f"(d[103]),
        "+f"(d[104]), "+f"(d[105]), "+f"(d[106]), "+f"(d[107]), "+f"(d[108]), "+f"(d[109]), "+f"(d[110]), "+f"(d[111]),
        "+f"(d[112]), "+f"(d[113]), "+f"(d[114]), "+f"(d[115]), "+f"(d[116]), "+f"(d[117]), "+f"(d[118]), "+f"(d[119]),
        "+f"(d[120]), "+f"(d[121]), "+f"(d[122]), "+f"(d[123]), "+f"(d[124]), "+f"(d[125]), "+f"(d[126]), "+f"(d[127])
      : "l"(da), "l"(db), "r"(accumulate));
}

struct Ring {
  uint64_t da, db;
  uint32_t slot, phase;
  uint32_t prev;
};
struct Attn {
  float S[32], O[16];
  uint32_t P[4][4], Q[2][4];
  float l0, l1, m0, m1;
  float t0, t1;
  uint64_t dk, dv;
  int it;
  int rare;
};
struct Ctx {
  int wg, warp, lane, rb, cb;
  bool leader;
};

template <bool B> struct RingCfg;
template <> struct RingCfg<false> { static constexpr uint32_t size = kSlotA, slots = kSlotsA, full = kSmem + kBarFullA; };
template <> struct RingCfg<true> { static constexpr uint32_t size = kSlotB, slots = kSlotsB, full = kSmem + kBarFullB; };

__device__ __forceinline__ uint64_t opaque(uint64_t v) {
  asm volatile("" : "+l"(v));
  return v;
}
template <bool B>
__device__ __forceinline__ void ring_reset(const Ctx& c, Ring& r) {
  r.da = opaque((B ? make_desc(kSmem, 128, 1024, 0) : make_desc(kSmem, 16, 1024, 1)) + c.wg * 512);
  r.db = opaque(make_desc(kSmem + 16384, 8192, 1024, 1));
  r.slot = 0;
  r.phase = 0;
  r.prev = kSmem + kBarDummy;
}
__device__ __forceinline__ void ring_release_prev(const Ctx& c, const Ring& r) {
  if (c.leader) mbar_arrive(r.prev);
}
template <bool B>
__device__ __forceinline__ uint32_t ring_full(const Ring& r) { return RingCfg<B>::full + 8 * r.slot; }
template <bool B>
__device__ __forceinline__ void ring_advance(Ring& r) {
  r.prev = ring_full<B>(r) + 8 * RingCfg<B>::slots;
  const uint32_t old = r.slot;
  if (++r.slot == RingCfg<B>::slots) { r.slot = 0; r.phase ^= 1; }
  if (B) {
    const uint64_t flip = (old ^ r.slot) * (kSlotB >> 4);
    r.da ^= flip;
    r.db ^= flip;
  } else {
    const uint32_t step = (r.slot - old) * (kSlotA >> 4);
    r.da ^= (uint32_t)r.da ^ ((uint32_t)r.da + step);
    r.db ^= (uint32_t)r.db ^ ((uint32_t)r.db + step);
  }
}
template <bool B, int K0, int K1, int R>
__device__ __forceinline__ void gemm_steps(float (&acc)[R], const Ring& r, int accumulate) {
#pragma unroll
  for (int k = K0; k < K1; k++) wgmma_ss(acc, r.da + k * (B ? 16 : 2), r.db + k * 128, k == 0 ? accumulate : 1);
}
template <bool B, int R>
__device__ __forceinline__ void stage_pure(const Ctx& c, Ring& r, float (&acc)[R], int accumulate) {
  mbar_wait(ring_full<B>(r), r.phase);
  wg_fence();
  gemm_steps<B, 0, 4>(acc, r, accumulate);
  wg_commit();
  wg_wait<1>();
  ring_release_prev(c, r);
  ring_advance<B>(r);
}
__device__ __forceinline__ void ring_drain(const Ctx& c, Ring& r) {
  wg_wait<0>();
  ring_release_prev(c, r);
  r.prev = kSmem + kBarDummy;
}
__device__ __forceinline__ void event_arrive(const Ctx& c, int ev) {
  asm volatile("{\n.reg .pred p;\nbar.warp.sync 0xffffffff;\nsetp.eq.u32 p, %1, 0;\n"
               "@p mbarrier.arrive.shared::cta.b64 _, [%0];\n}\n" ::"r"(kSmem + kBarEvent + 8 * ev), "r"(c.lane) : "memory");
}
__device__ __forceinline__ uint32_t gate_addr(const Ctx& c) {
  return kSmem + kOffGate + (c.wg * 64 + c.warp * 16 + (c.lane >> 2)) * 4;
}

__device__ __forceinline__ void attn_finish(const Ctx& c, Attn& a, int round) {
  pin(a.O);
  const float s0 = lds_f32(gate_addr(c)) * rcp(quad_sum(a.l0));
  const float s1 = lds_f32(gate_addr(c) + 32) * rcp(quad_sum(a.l1));
  uint8_t* dst = g_img + (size_t)(c.rb * 72 + 56 + round * 4 + (c.cb >> 1)) * 16384 + (c.wg * 8 + c.warp * 2) * 1024 + (c.cb & 1) * 512 + c.lane * 4;
#pragma unroll
  for (int j = 0; j < 4; j++) {
    const uint32_t lo = pack2(a.O[4 * j] * s0, a.O[4 * j + 1] * s0), hi = pack2(a.O[4 * j + 2] * s1, a.O[4 * j + 3] * s1);
    *reinterpret_cast<uint32_t*>(dst + j * 128) = lo;
    *reinterpret_cast<uint32_t*>(dst + j * 128 + 1024) = hi;
  }
  event_arrive(c, kEvO + round);
#pragma unroll
  for (int i = 0; i < 16; i++) a.O[i] = 0.f;
  a.l0 = 0.f;
  a.l1 = 0.f;
}
__device__ __forceinline__ const uint4* q_slot(int head) { return g_q + (blockIdx.x * 4 + head) * 512 + threadIdx.x; }
__device__ __forceinline__ void load_q(uint32_t (&q)[2][4], const uint4* src) {
  const uint4 q0 = __ldcg(src), q1 = __ldcg(src + 256);
  q[0][0] = q0.x; q[0][1] = q0.y; q[0][2] = q0.z; q[0][3] = q0.w;
  q[1][0] = q1.x; q[1][1] = q1.y; q[1][2] = q1.z; q[1][3] = q1.w;
}
__device__ __forceinline__ void attn_pv(Attn& a) {
#pragma unroll
  for (int t = 0; t < 4; t++) wgmma_rs_n32(a.O, a.P[t], a.dv + t * 64, 1);
}

template <bool FAST, bool B, int K0, int K1, int R>
__device__ __forceinline__ bool attn_step(const Ctx& c, Attn& a, Ring& r, float (&acc)[R], int accumulate, const uint4* q_head1) {
  a.l0 += a.t0;
  a.l1 += a.t1;
  wg_fence();
  wgmma_rs_n32(a.O, a.P[0], a.dv, 1);
  wgmma_rs_n64(a.S, a.Q[0], a.dk, 0);
  wgmma_rs_n32(a.O, a.P[1], a.dv + 64, 1);
  wgmma_rs_n64(a.S, a.Q[1], a.dk + 16, 1);
  wg_commit();
  wgmma_rs_n32(a.O, a.P[2], a.dv + 128, 1);
  wgmma_rs_n32(a.O, a.P[3], a.dv + 192, 1);
  wg_commit();
  gemm_steps<B, K0, K1>(acc, r, accumulate);
  wg_commit();
  wg_wait<2>();
  if (K0 == 0) ring_release_prev(c, r);
  if (K1 == 4) ring_advance<B>(r);
  pin(a.S);
  if (R == 128 && K1 == 4 && a.it == 31) load_q(a.Q, q_head1);
  const uint32_t kv_empty = kSmem + kBarEmptyK + 8 * (a.it & 3);
  const uint64_t flip = ((a.it ^ (a.it + 1)) & 3) * (kSlotK >> 4);
  a.dk ^= flip;
  a.dv ^= flip;
  float s0, s1, s2, s3;
  if (FAST) {
    float e[8];
#pragma unroll
    for (int i = 0; i < 8; i++) e[i] = ex2(a.S[i]);
    wg_wait<1>();
    if (c.leader) mbar_arrive(kv_empty);
#pragma unroll
    for (int i = 0; i < 32; i += 4) {
      const float p0 = i < 8 ? e[i] : ex2(a.S[i]), p1 = i < 8 ? e[i + 1] : ex2(a.S[i + 1]);
      const float p2 = i < 8 ? e[i + 2] : ex2(a.S[i + 2]), p3 = i < 8 ? e[i + 3] : ex2(a.S[i + 3]);
      if (i == 0) { s0 = p0; s1 = p1; s2 = p2; s3 = p3; } else { s0 += p0; s1 += p1; s2 += p2; s3 += p3; }
      a.P[i / 8][(i % 8) / 2] = pack2(p0, p1);
      a.P[i / 8][(i % 8) / 2 + 1] = pack2(p2, p3);
    }
  } else {
    wg_wait<1>();
    if (c.leader) mbar_arrive(kv_empty);
    pin(a.O);
    if ((a.it & 31) == 0 && a.it != 0) {
      attn_finish(c, a, (a.it >> 5) - 1);
      a.m0 = -INFINITY;
      a.m1 = -INFINITY;
    }
    float x0 = a.m0, x1 = a.m1;
#pragma unroll
    for (int i = 0; i < 32; i += 4) {
      x0 = fmaxf(x0, fmaxf(a.S[i], a.S[i + 1]));
      x1 = fmaxf(x1, fmaxf(a.S[i + 2], a.S[i + 3]));
    }
    x0 = fmaxf(x0, __shfl_xor_sync(~0u, x0, 1));
    x1 = fmaxf(x1, __shfl_xor_sync(~0u, x1, 1));
    x0 = fmaxf(x0, __shfl_xor_sync(~0u, x0, 2));
    x1 = fmaxf(x1, __shfl_xor_sync(~0u, x1, 2));
    const float a0 = ex2(a.m0 - x0), a1 = ex2(a.m1 - x1);
    a.m0 = x0;
    a.m1 = x1;
    a.l0 *= a0;
    a.l1 *= a1;
#pragma unroll
    for (int i = 0; i < 16; i += 4) { a.O[i] *= a0; a.O[i + 1] *= a0; a.O[i + 2] *= a1; a.O[i + 3] *= a1; }
#pragma unroll
    for (int i = 0; i < 32; i += 4) {
      const float p0 = ex2(a.S[i] - x0), p1 = ex2(a.S[i + 1] - x0), p2 = ex2(a.S[i + 2] - x1), p3 = ex2(a.S[i + 3] - x1);
      if (i == 0) { s0 = p0; s1 = p1; s2 = p2; s3 = p3; } else { s0 += p0; s1 += p1; s2 += p2; s3 += p3; }
      a.P[i / 8][(i % 8) / 2] = pack2(p0, p1);
      a.P[i / 8][(i % 8) / 2 + 1] = pack2(p2, p3);
    }
  }
  a.t0 = s0 + s1;
  a.t1 = s2 + s3;
  a.it++;
  bool ready = mbar_try(kSmem + kBarFullK + 8 * (a.it & 3), a.it >> 2);
  if (K1 == 4) ready &= mbar_try(ring_full<B>(r), r.phase);
  return ready;
}

__host__ __device__ constexpr int next_event(int it, int end) {
  const int e = it < 33 ? 33 : it < 64 ? 64 : it < 65 ? 65 : it < 96 ? 96 : it < 97 ? 97 : 128;
  return e < end ? e : end;
}
template <bool B, bool RING>
__device__ __forceinline__ void wait_operands(const Attn& a, const Ring& r) {
  if (RING) mbar_wait2(kSmem + kBarFullK + 8 * (a.it & 3), a.it >> 2, ring_full<B>(r), r.phase);
  else mbar_wait(kSmem + kBarFullK + 8 * (a.it & 3), a.it >> 2);
}
template <bool FAST, bool B, int BEGIN, int END, bool EVEN, bool ODD, bool RING>
__device__ __forceinline__ void attn_rare(const Ctx& c, Attn& a, Ring& r, bool ready, uint32_t (&qn)[2][4]) {
  constexpr auto in = [](int e) { return BEGIN < e && e < END; };
  constexpr bool swap = EVEN && (in(64) || in(96)), finish = ODD && (in(33) || in(65) || in(97));
  if ((swap || finish) && a.it == a.rare) {
    if (swap) {
#pragma unroll
      for (int i = 0; i < 8; i++)
        asm volatile("{\n.reg .pred p;\nsetp.eq.u32 p, %2, 0;\n@p mov.b32 %0, %1;\n}\n" : "+r"(a.Q[i / 4][i % 4]) : "r"(qn[i / 4][i % 4]), "r"(a.it & 1));
    }
    if (finish && (!swap || (a.it & 1))) {
      if (in(65) && a.it == 65) load_q(qn, q_slot(3));
      if (FAST) attn_finish(c, a, (a.it >> 5) - 1);
    }
    a.rare = next_event(a.it, END);
  }
  if (!ready) wait_operands<B, RING>(a, r);
}

template <bool FAST, bool B, int BEGIN, int END, bool FRESH, int R>
__device__ __forceinline__ void run_double(const Ctx& c, Attn& a, Ring& r, float (&acc)[R], uint32_t (&qn)[2][4]) {
  static_assert(BEGIN % 2 == 0 && END % 2 == 0 && next_event(BEGIN - 1, 128) != BEGIN, "bad phase boundary");
  const uint4* q_head1 = R == 128 ? reinterpret_cast<const uint4*>(opaque(reinterpret_cast<uint64_t>(q_slot(1)))) : nullptr;
  a.rare = next_event(BEGIN, END);
  wait_operands<B, true>(a, r);
#pragma unroll 1
  while (true) {
    bool ready;
#pragma unroll 1
    do {
      ready = attn_step<FAST, B, 0, 2>(c, a, r, acc, !FRESH || a.it != BEGIN, q_head1);
      if (!ready || a.it == a.rare) attn_rare<FAST, B, BEGIN, END, false, true, false>(c, a, r, ready, qn);
      ready = attn_step<FAST, B, 2, 4>(c, a, r, acc, 1, q_head1);
    } while (ready && a.it != a.rare);
    if (a.it == END) break;
    attn_rare<FAST, B, BEGIN, END, true, false, true>(c, a, r, ready, qn);
  }
}
template <bool FAST, int BEGIN, int END>
__device__ __forceinline__ void run_single(const Ctx& c, Attn& a, Ring& r, float (&acc)[64], uint32_t (&qn)[2][4]) {
  static_assert(next_event(BEGIN - 1, 128) != BEGIN, "bad phase boundary");
  a.rare = next_event(BEGIN, END);
  wait_operands<true, true>(a, r);
#pragma unroll 1
  while (true) {
    bool ready;
#pragma unroll 1
    do ready = attn_step<FAST, true, 0, 4>(c, a, r, acc, 1, nullptr);
    while (ready && a.it != a.rare);
    if (a.it == END) break;
    attn_rare<FAST, true, BEGIN, END, true, true, true>(c, a, r, ready, qn);
  }
}

__device__ __forceinline__ float scaled_silu(float x, float half_k) {
  float t;
  asm("tanh.approx.f32 %0, %1;" : "=f"(t) : "f"(0.5f * x));
  const float y = x * half_k;
  return fmaf(y, t, y);
}
template <int R>
__device__ __forceinline__ void store_h(const Ctx& c, float (&acc)[R], uint32_t stage, int ev) {
  pin(acc);
  uint32_t dst = kSmem + stage + (c.wg * 8 + c.warp * 2 + ((c.lane >> 3) & 1)) * 1024 + (c.lane >> 4) * 128 + (c.lane & 7) * 16;
  if (R == 96) mbar_wait(kSmem + kBarGate, 0);
  const float k0 = fmaf(lds_f32(gate_addr(c)), -0.5f, 0.5f), k1 = fmaf(lds_f32(gate_addr(c) + 32), -0.5f, 0.5f);
  constexpr int U = R == 96 ? 3 : 2;
#pragma unroll 1
  for (int trip = 0; trip < R / 32; trip += U) {
#pragma unroll
    for (int part = 0; part < U; part++) {
      const int chunk = trip + part;
      uint32_t u[16];
#pragma unroll
      for (int i = 0; i < 32; i += 4) {
        const float* v = acc + part * 32 + i;
        u[i / 2] = pack2(scaled_silu(v[0], k0), scaled_silu(v[1], k0));
        u[i / 2 + 1] = pack2(scaled_silu(v[2], k1), scaled_silu(v[3], k1));
      }
      if (part == U - 1) {
#pragma unroll
        for (int i = 0; i < R - 32 * U; i++) acc[i] = acc[i + 32 * U];
      }
      if (chunk > 0) {
        asm volatile("fence.proxy.async.shared::cta;" ::: "memory");
        event_arrive(c, ev + chunk - 1);
      }
      if (chunk < R / 32 - 2) mbar_wait(kSmem + kBarEmptyA + (R == 128 && chunk == 0 ? 16 : 24), 1);
#pragma unroll
      for (int j = 0; j < 4; j++)
        asm volatile("stmatrix.sync.aligned.m8n8.x4.shared.b16 [%0], {%1, %2, %3, %4};" ::"r"(dst + j * 256), "r"(u[4 * j]),
                     "r"(u[4 * j + 1]), "r"(u[4 * j + 2]), "r"(u[4 * j + 3])
                     : "memory");
      dst += 16384;
    }
  }
  asm volatile("fence.proxy.async.shared::cta;" ::: "memory");
  event_arrive(c, ev + R / 32 - 1);
}

template <bool FAST>
__device__ __forceinline__ void consumer_main(const Maps& maps, const Ctx& c, Attn& a, Ring& r, float (&acc_a)[96]) {
  using S = Sched<FAST>;
  uint32_t qn[2][4];
  run_double<FAST, false, 0, kItA, false>(c, a, r, acc_a, qn);
  ring_drain(c, r);
  store_h(c, acc_a, kStageHa, kEvHa);
  {
    float acc[128];
    run_double<FAST, false, kItA, kItA + kItB, true>(c, a, r, acc, qn);
    ring_drain(c, r);
    load_q(qn, q_slot(2));
    store_h(c, acc, kStageHb, kEvHb);
  }
  float acc[64];
  ring_reset<true>(c, r);
  run_double<FAST, true, kItA + kItB, S::single, true>(c, a, r, acc, qn);
  run_single<FAST, S::single, S::end>(c, a, r, acc, qn);
  mbar_wait(kSmem + kBarFullK + 8 * (S::end & 3), S::end >> 2);
  wg_fence();
  attn_pv(a);
  wg_commit();
  a.l0 += a.t0;
  a.l1 += a.t1;
  if (FAST) {
    constexpr int po = S::end + 1, pl = po + 1;
    static_assert((pl & 3) == (po & 3) + 1, "the two slots must be adjacent");
    mbar_wait(kSmem + kBarFullK + 8 * (pl & 3), pl >> 2);
    const uint32_t src = kSmem + kOffKv + (po & 3) * kSlotK;
    const uint4 p0 = lds_v4(src + threadIdx.x * 16), p1 = lds_v4(src + threadIdx.x * 16 + 4096);
    a.l0 += lds_f32(src + kSlotK + threadIdx.x * 4);
    a.l1 += lds_f32(src + kSlotK + threadIdx.x * 4 + 1024);
    wg_wait<0>();
    pin(a.O);
    const uint32_t p[8] = {p0.x, p0.y, p0.z, p0.w, p1.x, p1.y, p1.z, p1.w};
#pragma unroll
    for (int i = 0; i < 8; i++) { a.O[2 * i] += bf_lo(p[i]); a.O[2 * i + 1] += bf_hi(p[i]); }
  }
  wg_wait<0>();
  attn_finish(c, a, 3);
#pragma unroll 1
  for (int s = 68 - kPureTail; s < 72; s++) {
    if (s == 68 && c.wg == 1) asm volatile("bar.sync 3, 256;" ::: "memory");
    stage_pure<true>(c, r, acc, 1);
  }
  if (c.wg == 0) asm volatile("bar.arrive 3, 256;" ::: "memory");
  wg_wait<0>();
  pin(acc);
  const uint32_t stage = kSmem + kOffKv + c.wg * 16384;
  const int row = c.warp * 16 + (c.lane & 15);
#pragma unroll
  for (int j = 0; j < 16; j += 2) {
    const int col = j + (c.lane >> 4);
    const uint32_t addr = stage + (col >> 3) * 8192 + row * 128 + (((col & 7) ^ (row & 7)) << 4);
    asm volatile("stmatrix.sync.aligned.m8n8.x4.shared.b16 [%0], {%1, %2, %3, %4};" ::"r"(addr),
                 "r"(pack2(acc[4 * j], acc[4 * j + 1])), "r"(pack2(acc[4 * j + 2], acc[4 * j + 3])),
                 "r"(pack2(acc[4 * j + 4], acc[4 * j + 5])), "r"(pack2(acc[4 * j + 6], acc[4 * j + 7]))
                 : "memory");
  }
  asm volatile("fence.proxy.async.shared::cta;" ::: "memory");
  asm volatile("bar.sync %0, 128;" ::"r"(1 + c.wg) : "memory");
  if (c.leader) {
    tma3_store(&maps.out, stage, c.rb * 128 + c.wg * 64, c.cb * 2);
    asm volatile("cp.async.bulk.commit_group;\ncp.async.bulk.wait_group.read 0;" ::: "memory");
  }
}

__device__ __forceinline__ void consumer(const Maps& maps, const Ctx& c) {
  Ring r;
  ring_reset<false>(c, r);
  Attn a;
  unsigned qmax;
  uint4 park[6];
  {
    const int tok = c.rb * 128 + c.cb * 16 + (c.wg * 4 + c.warp) * 2;
    const int row = c.cb * 16 + (c.wg * 4 + c.warp) * 2;
    const uint32_t xs0 = kSmem + row * 128 + (((c.lane >> 2) ^ (row & 7)) << 4) + (c.lane & 3) * 4;
    const uint32_t xs1 = (xs0 + 128) ^ 16;
    float d0 = 0.f, d1 = 0.f;
    float acc[68];
#pragma unroll 1
    for (int s = 0; s < 16; s++) {
      stage_pure<false>(c, r, acc, s != 0);
      const uint32_t xa = lds_u32(xs0 + (s & 3) * kSlotA), xb = lds_u32(xs1 + (s & 3) * kSlotA);
      const uint32_t gw = lds_u32(kSmem + kOffKv + s * 128 + c.lane * 4);
      d0 = fmaf(bf_lo(xa), bf_lo(gw), fmaf(bf_hi(xa), bf_hi(gw), d0));
      d1 = fmaf(bf_lo(xb), bf_lo(gw), fmaf(bf_hi(xb), bf_hi(gw), d1));
    }
    ring_drain(c, r);
    pin(acc);
    const bool is_v = c.cb >= 4;
    const uint32_t u0 = pack2(acc[64], acc[65]), u1 = pack2(acc[66], acc[67]);
    uint8_t* kv = g_kv + ((c.rb * 2 + c.wg + is_v) & 31) * 8192 + is_v * 4096 + c.warp * 1024 + (c.cb & 3) * 128 + c.lane * 4;
    *reinterpret_cast<uint32_t*>(kv) = u0;
    *reinterpret_cast<uint32_t*>(kv + 512) = u1;
    const float n0 = quad_sum(bf_lo(u0) * bf_lo(u0) + bf_hi(u0) * bf_hi(u0));
    const float n1 = quad_sum(bf_lo(u1) * bf_lo(u1) + bf_hi(u1) * bf_hi(u1));
    const unsigned v_abs = max(max(u0 << 16 & 0x7fff0000u, u0 & 0x7fff0000u), max(u1 << 16 & 0x7fff0000u, u1 & 0x7fff0000u));
    const unsigned st_max = __reduce_max_sync(~0u, is_v ? v_abs : max(__float_as_uint(n0), __float_as_uint(n1)));
    if (c.lane == 0) sts_u32(kSmem + kOffStat + (c.wg * 4 + c.warp) * 4, st_max);
    event_arrive(c, kEvKv);
#pragma unroll
    for (int o = 16; o > 0; o >>= 1) {
      d0 += __shfl_xor_sync(~0u, d0, o);
      d1 += __shfl_xor_sync(~0u, d1, o);
    }
    if (c.lane < 2) g_gate[tok + c.lane] = sigmoid(c.lane ? d1 : d0);
    qmax = 0;
#pragma unroll
    for (int h = 0; h < 4; h++) {
      uint32_t f[8];
      float n0 = 0.f, n1 = 0.f;
#pragma unroll
      for (int i = 0; i < 8; i++) {
        const float q0 = acc[16 * h + 2 * i] * kScale, q1 = acc[16 * h + 2 * i + 1] * kScale;
        f[i] = pack2(q0, q1);
        if (i & 1) n1 = fmaf(q0, q0, fmaf(q1, q1, n1)); else n0 = fmaf(q0, q0, fmaf(q1, q1, n0));
      }
      qmax = max(qmax, max(__float_as_uint(quad_sum(n0)), __float_as_uint(quad_sum(n1))));
      if (h == 0) {
#pragma unroll
        for (int i = 0; i < 8; i++) a.Q[i / 4][i % 4] = f[i];
      } else {
        park[2 * h - 2] = make_uint4(f[0], f[1], f[2], f[3]);
        park[2 * h - 1] = make_uint4(f[4], f[5], f[6], f[7]);
      }
    }
  }
  qmax = __reduce_max_sync(~0u, qmax);
  if (c.lane == 0) sts_u32(kSmem + kOffQmax + (c.wg * 4 + c.warp) * 4, qmax);
  event_arrive(c, kEvGate);
  float acc_a[96];
#pragma unroll 1
  for (int s = 0; s < kPureHead; s++) stage_pure<false>(c, r, acc_a, s != 0);
#pragma unroll
  for (int i = 0; i < 6; i++) const_cast<uint4*>(q_slot(1))[i * 256] = park[i];
  event_arrive(c, kEvQ);
#pragma unroll
  for (int i = 0; i < 16; i++) { a.P[i / 4][i % 4] = 0; a.O[i] = 0.f; }
  a.l0 = 0.f; a.l1 = 0.f; a.t0 = 0.f; a.t1 = 0.f;
  a.m0 = -INFINITY; a.m1 = -INFINITY;
  a.it = 0;
  a.dk = opaque(make_desc(kSmem + kOffKv, 128, 512, 0));
  a.dv = opaque(make_desc(kSmem + kOffKv + 4096, 512, 128, 0));
  mbar_wait(kSmem + kBarMeta, 0);
  const bool fast = lds_u32(kSmem + kOffMode);
  if (__any_sync(~0u, !fast)) consumer_main<false>(maps, c, a, r, acc_a);
  else consumer_main<true>(maps, c, a, r, acc_a);
}

__device__ __forceinline__ void assist_publish(const Ctx& c, float (&O)[16], float l0, float l1, int n) {
  pin(O);
  uint8_t* dst = g_part + (blockIdx.x - kCtas + n * kAssistCtas) * kPartBytes;
  reinterpret_cast<uint4*>(dst)[threadIdx.x] = make_uint4(pack2(O[0], O[1]), pack2(O[2], O[3]), pack2(O[4], O[5]), pack2(O[6], O[7]));
  reinterpret_cast<uint4*>(dst)[threadIdx.x + 256] = make_uint4(pack2(O[8], O[9]), pack2(O[10], O[11]), pack2(O[12], O[13]), pack2(O[14], O[15]));
  reinterpret_cast<float*>(dst + kSlotK)[threadIdx.x] = l0;
  reinterpret_cast<float*>(dst + kSlotK)[threadIdx.x + 256] = l1;
  event_arrive(c, c.wg * 4 + (n & 3));
}
__device__ __forceinline__ void assist_consumer(const Ctx& c) {
  constexpr int kItems = kCtas / kAssistCtas;
  float S[32], O[16], l0 = 0.f, l1 = 0.f;
  uint32_t P[4][4], Q[2][4], qn[2][4];
  const uint4* qp = g_q + ((blockIdx.x - kCtas) * 4 + 3) * 512 + threadIdx.x;
#pragma unroll
  for (int i = 0; i < 16; i++) { P[i / 4][i % 4] = 0; O[i] = 0.f; }
  if (threadIdx.x == 0) {
    __nanosleep(5000);
    flag_wait(g_flag + kFlagQ, kCtas);
    mbar_expect(kSmem + kBarFullK, (kAssist + 1) * kSlotK);
    bulk_load(kSmem, g_kv + (32 - kAssist) * kSlotK, kAssist * kSlotK, kSmem + kBarFullK);
    bulk_load(kSmem + kAssist * kSlotK, g_kv, kSlotK, kSmem + kBarFullK);
  }
  __syncwarp();
  mbar_wait(kSmem + kBarFullK, 0);
  load_q(Q, qp);
#pragma unroll 1
  for (int n = 0; n < kItems; n++) {
#pragma unroll
    for (int t = 0; t < kAssist; t++) {
      const uint64_t dk = make_desc(kSmem + t * kSlotK, 128, 512, 0);
      const uint64_t dv = make_desc(kSmem + (t == 0 ? kAssist : t) * kSlotK + 4096, 512, 128, 0);
      wg_fence();
      wgmma_rs_n64(S, Q[0], dk, 0);
      wgmma_rs_n64(S, Q[1], dk + 16, 1);
      wg_commit();
#pragma unroll
      for (int k = 0; k < 4; k++) wgmma_rs_n32(O, P[k], dv + k * 64, k != 0 || t != 1);
      wg_commit();
      if (t == 0) load_q(qn, qp + min(n + 1, kItems - 1) * kAssistCtas * 2048);
      wg_wait<0>();
      pin(S);
      if (t == 0) {
        if (n > 0) assist_publish(c, O, l0, l1, n - 1);
        l0 = 0.f;
        l1 = 0.f;
      }
      if (t == kAssist - 1) {
#pragma unroll
        for (int i = 0; i < 8; i++) Q[i / 4][i % 4] = qn[i / 4][i % 4];
      }
#pragma unroll
      for (int i = 0; i < 32; i += 4) {
        const float p0 = ex2(S[i]), p1 = ex2(S[i + 1]), p2 = ex2(S[i + 2]), p3 = ex2(S[i + 3]);
        l0 += p0 + p1;
        l1 += p2 + p3;
        P[i / 8][(i % 8) / 2] = pack2(p0, p1);
        P[i / 8][(i % 8) / 2 + 1] = pack2(p2, p3);
      }
    }
  }
  wg_fence();
#pragma unroll
  for (int k = 0; k < 4; k++) wgmma_rs_n32(O, P[k], make_desc(kSmem + kAssist * kSlotK + 4096, 512, 128, 0) + k * 64, 1);
  wg_commit();
  wg_wait<0>();
  assist_publish(c, O, l0, l1, kItems - 1);
}

__device__ __forceinline__ void gemm_producer(const Maps& maps, uint32_t smem, int rb, int cb) {
  const uint64_t once = policy_evict_first();
#pragma unroll 1
  for (int s = kSlotsA; s < 48; s++) {
    const uint32_t full = smem + kBarFullA + 8 * (s & 3), dst = smem + (s & 3) * kSlotA;
    const int k0 = (s & 15) * 64, pass = s >> 4;
    mbar_wait(s == 35 ? smem + kBarDrained : full + 8 * kSlotsA, s == 35 ? 0 : ~(s >> 2) & 1);
    if (pass) mbar_arrive(full);
    mbar_expect(full, 32768 + pass * 8192);
    tma2(dst, &maps.x, k0, rb * 128, full);
    tma3(dst + 16384, &maps.wq + pass, k0, pass ? cb * 7 + 3 * pass - 3 : cb * 2, full, once);
  }
  uint32_t slot = 0, phase = 1;
  int chunk = 0, left = 3;
  const uint8_t* img = g_img + rb * 72 * 16384;
#pragma unroll 1
  for (int s = 0; s < 68; s++) {
    const uint32_t full = smem + kBarFullB + 8 * slot, dst = smem + slot * kSlotB;
    if (s >= 6) mbar_wait(full + 8 * kSlotsB, phase);
    else mbar_wait(s >= 4 ? smem + kBarDrained + 8 : smem + kBarEmptyA + 8 * ((s + 1) >> 1), s < 4);
    mbar_expect(full, 32768);
    if (s < 56) {
      tma3(dst + 16384, &maps.w2, chunk * 64, cb * 2, full, once);
      chunk++;
      if (--left == 0) {
        left = s < 23 ? 3 : 4;
        chunk = s == 23 ? 3 : chunk + 7 - left;
      }
    } else {
      tma5(dst + 16384, &maps.wo, (s & 3) * 2, (s - 56) >> 2, cb * 2, full, once);
    }
    if (s == 0 || s == 24 || s == 56 || s == 60 || s == 64)
      flag_wait(g_flag + rb * 32 + (s < 56 ? (s ? kFlagHb : kFlagHa) : kFlagO + ((s - 56) >> 2)), 8);
    bulk_load(dst, img + s * 16384, 16384, full);
    if (++slot == kSlotsB) { slot = 0; phase ^= 1; }
  }
  constexpr uint32_t first = 68 % kSlotsB;
  int nw = 0, no = 0, spins = 0;
  bool seen = false;
#pragma unroll 1
  while (no < 4 && ++spins < 0x40000) {
    const uint32_t full = smem + kBarFullB + 8 * first, dst = smem + first * kSlotB;
    if (nw < 4 && mbar_try(full + 8 * (kSlotsB + nw), phase)) {
      mbar_expect(full + 8 * nw, 32768);
      tma5(dst + nw * kSlotB + 16384, &maps.wo, nw * 2, 3, cb * 2, full + 8 * nw, once);
      nw++;
    } else if (!seen) {
      unsigned v;
      asm volatile("ld.relaxed.gpu.global.u32 %0, [%1];" : "=r"(v) : "l"(g_flag + rb * 32 + kFlagO + 3) : "memory");
      seen = v >= 8;
      if (seen) asm volatile("fence.acquire.gpu;\nfence.proxy.async.global;" ::: "memory");
    }
    if (seen && no < nw) {
      bulk_load(dst + no * kSlotB, img + (68 + no) * 16384, 16384, full + 8 * no);
      no++;
    }
  }
  mbar_wait(smem + kBarPart, 0);
  if (atomicAdd(g_flag + kFlagDone, 1) == kCtas - 1) {
#pragma unroll 1
    for (int i = 0; i < kFlagWords; i += 32) {
      *reinterpret_cast<uint4*>(g_flag + i) = make_uint4(0, 0, 0, 0);
      *reinterpret_cast<uint4*>(g_flag + i + 4) = make_uint4(0, 0, 0, 0);
    }
  }
}

__device__ __forceinline__ void kv_producer(uint32_t smem, bool assist) {
  mbar_wait(smem + kBarEvent + 8 * kEvGate, 0);
  const float qbound = __uint_as_float(max(max4(lds_v4(smem + kOffQmax)), max4(lds_v4(smem + kOffQmax + 16)))) * (4.f * 1.02f);
  uint4 f;
  int spins = 0;
  do {
    asm volatile("ld.relaxed.gpu.global.v4.u32 {%0, %1, %2, %3}, [%4];" : "=r"(f.x), "=r"(f.y), "=r"(f.z), "=r"(f.w) : "l"(g_flag + kFlagKv) : "memory");
  } while (f.x < kCtas && ++spins < 0x20000);
  asm volatile("fence.acquire.gpu;\nfence.proxy.async.global;" ::: "memory");
  const float vm = __uint_as_float(f.z);
  const bool fast = assist && vm >= kMinV && vm <= kMaxV && qbound * __uint_as_float(f.y) <= kMaxScore * kMaxScore;
  const int end = fast ? Sched<true>::end : 128;
#pragma unroll 1
  for (int it = 0; it <= end; it++) {
    const uint32_t full = smem + kBarFullK + 8 * (it & 3);
    mbar_wait(full + 8 * kSlotsK, ~(it >> 2) & 1);
    mbar_expect(full, kSlotK);
    bulk_load(smem + kOffKv + (it & 3) * kSlotK, g_kv + (it & 31) * kSlotK, kSlotK, full);
    if (it == 0) {
      sts_u32(smem + kOffMode, fast);
      mbar_arrive(smem + kBarMeta);
    }
  }
  if (assist) {
    flag_wait(g_part_flag + blockIdx.x * 8, 2);
    g_part_flag[blockIdx.x * 8] = 0;
  }
  if (fast) {
    constexpr int po = Sched<true>::end + 1, pl = po + 1;
    constexpr uint32_t full = kBarFullK + 8 * (pl & 3);
    mbar_wait2(smem + kBarEmptyK + 8 * (po & 3), ~(po >> 2) & 1, smem + kBarEmptyK + 8 * (pl & 3), ~(pl >> 2) & 1);
    mbar_expect(smem + full, kPartBytes);
    bulk_load(smem + kOffKv + (po & 3) * kSlotK, g_part + blockIdx.x * kPartBytes, kPartBytes, smem + full);
  }
  mbar_arrive(smem + kBarPart);
}

__device__ __forceinline__ void load_raw(uint32_t smem, const __nv_bfloat16* wkv, int s, int slot) {
  mbar_expect(smem + kBarRaw + 8 * slot, 4096);
  bulk_load(smem + kOffRaw + slot * 4096, wkv + s * 2048, 4096, smem + kBarRaw + 8 * slot);
}
__device__ __forceinline__ void helper(uint32_t smem, const __nv_bfloat16* wkv, int rb, int cb, int lane) {
  const uint32_t src = smem + kOffRaw + lane * 64 + (cb & 3) * 16;
  const uint32_t dst = smem + 32768 + lane * 128 + ((lane & 7) << 4);
  uint32_t slot = 0, phase = 0;
#pragma unroll 1
  for (int s = 0; s < 16; s++) {
    const uint32_t d = dst + (s & 3) * kSlotA;
    mbar_wait(smem + kBarRaw + 8 * slot, phase);
    const uint4 v0 = lds_v4(src + slot * 4096), v1 = lds_v4(src + slot * 4096 + 2048);
    mbar_wait(smem + kBarEmptyA + 8 * (s & 3), ~(s >> 2) & 1);
    sts_v4(d, v0);
    sts_v4(d + 4096, v1);
    asm volatile("fence.proxy.async.shared::cta;" ::: "memory");
    __syncwarp();
    if (elect_one()) {
      mbar_arrive(smem + kBarFullA + 8 * (s & 3));
      if (s + kSlotsRaw < 16) load_raw(smem, wkv, s + kSlotsRaw, slot);
    }
    __syncwarp();
    if (++slot == kSlotsRaw) { slot = 0; phase ^= 1; }
  }
  if (lane == 0) {
    mbar_wait(smem + kBarEvent + 8 * kEvGate, 0);
    flag_wait(g_flag + kFlagGate + rb * 32, 8);
  }
  __syncwarp();
  sts_v4(smem + kOffGate + lane * 16, __ldcg(reinterpret_cast<const uint4*>(g_gate) + rb * 32 + lane));
  __syncwarp();
  if (lane == 0) mbar_arrive(smem + kBarGate);
}

__device__ __forceinline__ void signaller(uint32_t smem, int rb, int cb, int spare_wg) {
  constexpr uint64_t events = kEvKv | kEvGate << 4 | kEvQ << 8 | kEvHa << 12 | kEvO << 16 | kEvHb << 20 | (kEvO + 1) << 24 |
                              (uint64_t)(kEvO + 2) << 28 | (uint64_t)(kEvO + 3) << 32;
  constexpr uint64_t words = kFlagGate << 4 | kFlagHa << 12 | kFlagO << 16 | kFlagHb << 20 | (kFlagO + 1) << 24 |
                             (uint64_t)(kFlagO + 2) << 28 | (uint64_t)(kFlagO + 3) << 32;
  const bool spare = spare_wg >= 0;
#pragma unroll 1
  for (int e = 0; e < (spare ? kCtas / kAssistCtas : 9); e++) {
    const int ev = spare ? spare_wg * 4 + (e & 3) : (events >> 4 * e) & 15;
    unsigned* flag = spare ? g_part_flag + (blockIdx.x - kCtas + e * kAssistCtas) * 8
                           : g_flag + ((e | 2) == 2 ? kFlagKv + e * 16 : rb * 32) + ((words >> 4 * e) & 15);
    mbar_wait(smem + kBarEvent + 8 * ev, spare ? e >> 2 : 0);
    if (!spare && (e == 3 || e == 5)) {
      const int b = e >> 2;
      uint8_t* dst = g_img + (rb * 72 + (b ? 24 + cb * 4 : cb * 3)) * 16384;
#pragma unroll 1
      for (int i = 0; i < 3 + b; i++) {
        mbar_wait(smem + kBarEvent + 8 * (ev + i), 0);
        bulk_store(dst + i * 16384, smem + (b ? kStageHb : kStageHa) + i * 16384, 16384);
      }
      asm volatile("cp.async.bulk.commit_group;\ncp.async.bulk.wait_group.read 0;" ::: "memory");
      mbar_arrive(smem + kBarDrained + 8 * b);
      asm volatile("cp.async.bulk.wait_group 0;\nfence.proxy.async.global;" ::: "memory");
    }
    if (!spare && e == 0) atomicMax(flag + 1 + (cb >> 2), max(max4(lds_v4(smem + kOffStat)), max4(lds_v4(smem + kOffStat + 16))));
    flag_signal(flag);
  }
}

__global__ void __launch_bounds__(kThreads, 1)
fused_kernel(const __grid_constant__ Maps maps, const __grid_constant__ Weights w) {
  extern __shared__ __align__(1024) uint8_t smem_raw[];
  if ((uint32_t)__cvta_generic_to_shared(smem_raw) != kSmem) __trap();
  constexpr uint32_t smem = kSmem;
  const int warp = __shfl_sync(~0u, threadIdx.x >> 5, 0);
  const int rb = ((blockIdx.x >> 1) & 7) | ((blockIdx.x >> 3) & 8), cb = (blockIdx.x & 1) | ((blockIdx.x >> 3) & 6);
  const bool spare = blockIdx.x >= kCtas;
  const __nv_bfloat16* wkv = cb < 4 ? w.wk : w.wv;
  if (warp == 8) {
    if (elect_one()) {
#pragma unroll
      for (int s = 0; s < 2 * kSlotsA; s++) mbar_init(smem + kBarFullA + 8 * s, 2);
      asm volatile("fence.mbarrier_init.release.cluster;" ::: "memory");
      const uint64_t once = policy_evict_first();
#pragma unroll 1
      for (int s = 0; s < (spare ? 0 : kSlotsA); s++) {
        mbar_expect(smem + kBarFullA + 8 * s, s == 0 ? 32768 + 2048 : 32768);
        tma2(smem + s * kSlotA, &maps.x, s * 64, rb * 128, smem + kBarFullA + 8 * s);
        tma3(smem + s * kSlotA + 16384, &maps.wq, s * 64, cb * 2, smem + kBarFullA + 8 * s, once);
        if (s == 0) bulk_load(smem + kOffKv, w.gate, 2048, smem + kBarFullA);
      }
    }
  } else if (warp == 9) {
    if (elect_one()) {
#pragma unroll
      for (uint32_t b = kBarFullB; b < kBarEvent; b += 8) mbar_init(smem + b, (b >= kBarEmptyB && b < kBarFullK) || b >= kBarEmptyK ? 2 : 1);
      asm volatile("fence.mbarrier_init.release.cluster;" ::: "memory");
    }
  } else if (warp == 11) {
    if (elect_one()) {
#pragma unroll
      for (int s = 0; s < kSlotsRaw; s++) mbar_init(smem + kBarRaw + 8 * s, 1);
      asm volatile("fence.mbarrier_init.release.cluster;" ::: "memory");
#pragma unroll 1
      for (int s = 0; s < (spare ? 0 : kSlotsRaw); s++) load_raw(smem, wkv, s, s);
    }
  } else if (warp == 10) {
    if (elect_one()) {
#pragma unroll
      for (uint32_t b = kBarEvent; b <= kBarGate; b += 8) mbar_init(smem + b, b < kBarDrained ? (spare ? 4 : 8) : 1);
      asm volatile("fence.mbarrier_init.release.cluster;" ::: "memory");
    }
  }
  __syncthreads();
  if (warp < 8) {
    asm volatile("setmaxnreg.inc.sync.aligned.u32 240;");
    const Ctx c{warp >> 2, warp & 3, (int)(threadIdx.x & 31), rb, cb, (threadIdx.x & 127) == 0};
    if (spare) assist_consumer(c);
    else consumer(maps, c);
  } else {
    asm volatile("setmaxnreg.dec.sync.aligned.u32 24;");
    if (warp == 8) {
      if (!spare && elect_one()) gemm_producer(maps, smem, rb, cb);
    } else if (warp == 9) {
      if (!spare && elect_one()) kv_producer(smem, w.assist);
    } else if (warp == 10 || spare) {
      if (elect_one()) signaller(smem, rb, cb, spare ? warp - 10 : -1);
    } else {
      helper(smem, wkv, rb, cb, threadIdx.x & 31);
    }
  }
}

using EncodeFn = CUresult (*)(CUtensorMap*, CUtensorMapDataType, cuuint32_t, void*, const cuuint64_t*, const cuuint64_t*,
                              const cuuint32_t*, const cuuint32_t*, CUtensorMapInterleave, CUtensorMapSwizzle,
                              CUtensorMapL2promotion, CUtensorMapFloatOOBfill);

void encode(EncodeFn fn, CUtensorMap* map, const void* base, int rank, const cuuint64_t* dims, const cuuint64_t* strides,
            const cuuint32_t* box) {
  const cuuint32_t ones[5] = {1, 1, 1, 1, 1};
  fn(map, CU_TENSOR_MAP_DATA_TYPE_BFLOAT16, rank, const_cast<void*>(base), dims, strides, box, ones, CU_TENSOR_MAP_INTERLEAVE_NONE,
     CU_TENSOR_MAP_SWIZZLE_128B, CU_TENSOR_MAP_L2_PROMOTION_L2_128B, CU_TENSOR_MAP_FLOAT_OOB_FILL_NONE);
}
void encode_chunked(EncodeFn fn, CUtensorMap* map, const void* base, int rows, int cols, int chunks) {
  const cuuint64_t dims[3] = {64, (cuuint64_t)rows, (cuuint64_t)cols / 64};
  const cuuint64_t strides[2] = {(cuuint64_t)cols * 2, 128};
  const cuuint32_t box[3] = {64, 64, (cuuint32_t)chunks};
  encode(fn, map, base, 3, dims, strides, box);
}
void encode_plain(EncodeFn fn, CUtensorMap* map, const void* base, int rows, int cols, int box_rows) {
  const cuuint64_t dims[2] = {(cuuint64_t)cols, (cuuint64_t)rows};
  const cuuint64_t strides[1] = {(cuuint64_t)cols * 2};
  const cuuint32_t box[2] = {64, (cuuint32_t)box_rows};
  encode(fn, map, base, 2, dims, strides, box);
}

}

extern "C" void kernel_launch(void* const* d_in, const int* in_sizes, int n_in, void* d_out, int out_size) {
  (void)in_sizes; (void)n_in; (void)out_size;
  void* fn_ptr = nullptr;
  cudaDriverEntryPointQueryResult status;
  cudaGetDriverEntryPoint("cuTensorMapEncodeTiled", &fn_ptr, cudaEnableDefault, &status);
  const EncodeFn fn = reinterpret_cast<EncodeFn>(fn_ptr);
  Maps maps;
  encode_plain(fn, &maps.x, d_in[0], 2048, 1024, 128);
  encode_chunked(fn, &maps.wq, d_in[1], 1024, 1024, 2);
  encode_chunked(fn, &maps.w1a, d_in[6], 1024, 3584, 3);
  encode_chunked(fn, &maps.w1b, d_in[6], 1024, 3584, 4);
  encode_chunked(fn, &maps.w2, d_in[7], 3584, 1024, 2);
  {
    const cuuint64_t dims[5] = {64, 32, 8, 4, 16};
    const cuuint64_t strides[4] = {2048, 128 * 2048, 32 * 2048, 128};
    const cuuint32_t box[5] = {64, 32, 2, 1, 2};
    encode(fn, &maps.wo, d_in[4], 5, dims, strides, box);
  }
  encode_chunked(fn, &maps.out, d_out, 2048, 1024, 2);
  cudaFuncSetAttribute(fused_kernel, cudaFuncAttributeMaxDynamicSharedMemorySize, kSmemBytes);
  const auto in = [&](int i) { return static_cast<const __nv_bfloat16*>(d_in[i]); };
  int device = 0, sms = 0;
  cudaGetDevice(&device);
  cudaDeviceGetAttribute(&sms, cudaDevAttrMultiProcessorCount, device);
  const Weights w{in(2), in(3), in(8), sms >= kCtas + kAssistCtas};
  fused_kernel<<<kCtas + (w.assist ? kAssistCtas : 0), kThreads, kSmemBytes>>>(maps, w);
}
```
